```python
import torch

def _softmax(x, axis=-1):
    return torch.softmax(x, dim=axis)
def _gelu(x):
    return torch.nn.functional.gelu(x, approximate="tanh")
def _silu(x):
    return torch.nn.functional.silu(x)
def _sigmoid(x):
    return torch.sigmoid(x)
def _layernorm(x, axis=-1, eps=1e-5):
    m = x.mean(dim=axis, keepdim=True)
    v = x.var(dim=axis, keepdim=True, unbiased=False)
    return (x - m) / torch.sqrt(v + eps)
def _scatter_add(tgt, idx, src, axis=0):
    return tgt.clone().index_add_(axis, idx, src)
def _segment_sum(src, seg, n):
    out = torch.zeros((n,) + src.shape[1:], dtype=src.dtype)
    return out.index_add_(0, seg, src)
def _pad(x, pw):
    flat = tuple(v for pair in reversed(pw) for v in pair)
    return torch.nn.functional.pad(x, flat)

kernel_name = 'parallel_sum__sliding_local_dilated__mixer_channel_mlp__prompt'

def setup_inputs():

    _w = (lambda a: (lambda t: t.to(torch.bfloat16) if t.is_floating_point() else t)(torch.as_tensor(a)))
    def _A_setup():
        B, S, D = 1, 2048, 640
        return {
            "x": _w((lambda *s: torch.randn(*s, dtype=torch.bfloat16) * 0.05)(B, S, D)),
            "wqkv": _w((lambda *s: torch.randn(*s, dtype=torch.bfloat16) * 0.05)(D, 3 * D)),
            "wo": _w((lambda *s: torch.randn(*s, dtype=torch.bfloat16) * 0.05)(D, D)),
        }
    _A_in = _A_setup()

    def _B_setup():
        B, S, D, F = 1, 2048, 640, 1728
        return {
            "x": _w((lambda *s: torch.randn(*s, dtype=torch.bfloat16) * 0.05)(B, S, D)),
            "w1": _w((lambda *s: torch.randn(*s, dtype=torch.bfloat16) * 3.2)(D, F) * (D ** -0.5)),
            "b1": _w((lambda *s: torch.randn(*s, dtype=torch.bfloat16) * 1.6)(F)),
            "w2": _w((lambda *s: torch.randn(*s, dtype=torch.bfloat16) * 0.2)(F, D) * (F ** -0.5)),
            "b2": _w((lambda *s: torch.randn(*s, dtype=torch.bfloat16) * 0.4)(D)),
        }
    _B_in = _B_setup()

    return {
        "A_x": _A_in["x"],
        "A_wqkv": _A_in["wqkv"],
        "A_wo": _A_in["wo"],
        "B_x": _B_in["x"],
        "B_w1": _B_in["w1"],
        "B_b1": _B_in["b1"],
        "B_w2": _B_in["w2"],
        "B_b2": _B_in["b2"],
    }

def reference(A_x, A_wqkv, A_wo, B_x, B_w1, B_b1, B_w2, B_b2):
    def _A_ref(x, wqkv, wo):
        B, S, D = x.shape
        H = 32; Dh = D // H
        W, dil = 8, 2
        qkv = (lambda x, *d: x.permute(*d))((x @ wqkv).reshape(B, S, 3, H, Dh), 2, 0, 3, 1, 4)
        q, k, v = qkv[0], qkv[1], qkv[2]
        scale = Dh ** -0.5
        pos = torch.arange(S)
        off = torch.arange(W) * dil
        idx = pos[:, None] - off[None, :]
        mask = idx >= 0
        idx_c = torch.where(mask, idx, 0).reshape(-1)
        kg = k[:, :, idx_c, :].reshape(B, H, S, W, Dh)
        vg = v[:, :, idx_c, :].reshape(B, H, S, W, Dh)
        logits = torch.einsum("bhsd,bhswd->bhsw", q, kg) * scale
        logits = torch.where(mask[None, None, :, :], logits, -1e9)
        attn = _softmax(logits, axis=-1)
        o = torch.einsum("bhsw,bhswd->bhsd", attn, vg)
        return (lambda x, *d: x.permute(*d))(o, 0, 2, 1, 3).reshape(B, S, D) @ wo

    def _B_ref(x, w1, b1, w2, b2):
        y = _layernorm(x, axis=-1)
        h = _gelu(torch.einsum("bsd,df->bsf", y, w1) + b1)
        return torch.einsum("bsf,fd->bsd", h, w2) + b2

    x = A_x
    xn = _layernorm(x, axis=-1)
    return x + _A_ref(xn, A_wqkv, A_wo) + _B_ref(xn, B_w1, B_b1, B_w2, B_b2)
```

```cpp
#include <cuda_runtime.h>
#include <cuda_bf16.h>
#include <cuda.h>
#include <stdint.h>

#define FK_MAP 0
#define FK_ATT_Q 5
#define FK_HALO_Q 2

namespace fk {

typedef __nv_bfloat16 bf16;

constexpr int kS = 2048, kD = 640, kF = 1728;
constexpr int kThreads = 384;
constexpr int kCtas = 128;

constexpr uint32_t A_SLOT = 16384, A_N = 4;
constexpr uint32_t B_SLOT = 16384, B_N = 6;
constexpr uint32_t OFF_A = 0;
constexpr uint32_t OFF_B = OFF_A + A_N * A_SLOT;
constexpr uint32_t OFF_STG = OFF_B + B_N * B_SLOT;
constexpr uint32_t STG_BYTES = 3 * 16384 + 8192;
constexpr uint32_t B2_SLOT = 12288, B2_N = 8;
constexpr int B2_STEPS = 37;
constexpr uint32_t OFF_C = OFF_STG + STG_BYTES;
constexpr uint32_t OFF_CB = OFF_C + 240 * 4;
constexpr uint32_t OFF_RED = OFF_CB + 112 * 8;
constexpr uint32_t OFF_CQ = OFF_RED + 1024;
constexpr uint32_t OFF_B2 = OFF_CQ + 480;
constexpr uint32_t OFF_BAR = OFF_B2 + 160;
constexpr uint32_t OFF_XR = OFF_STG + 24576;
constexpr uint32_t KV_PITCH = 336;

enum : uint32_t {
  BAR_A_FULL = 0, BAR_A_EMPTY = 4,
  BAR_B_FULL = 8, BAR_B_EMPTY = 14, BAR_B_PEER = 20,
  BAR_B2_FULL = 26, BAR_B2_EMPTY = 34, BAR_B2_PEER = 42,
  BAR_PROL = 50, BAR_AUX, BAR_KV, BAR_HALO_R, BAR_HALO_W, BAR_O_W, BAR_H_ST0, BAR_H_ST1, BAR_HDONE,
  BAR_CS_FULL, BAR_H_RDY, BAR_O_RDY, BAR_CS2_FULL, BAR_PROL2, BAR_AUX2, BAR_ATT, BAR_EPOCH, BAR_XR, BAR_XROWS, BAR_ZERO, BAR_COUNT
};
static_assert(BAR_COUNT <= 72, "12 warps x 6 barriers");
constexpr uint32_t OFF_EPOCH = OFF_BAR + 72 * 8;
constexpr uint32_t SMEM_BYTES = OFF_EPOCH + 16;

constexpr int FL_DONE = 0, FL_O = 1, FL_H = FL_O + 32, FL_Z = FL_H + 128, FL_COUNT = FL_Z + 64;

__device__ __align__(1024) bf16 g_o[kS * kD];
__device__ __align__(1024) bf16 g_h[kS * kF];
__device__ uint4 g_stats[kS];
__device__ uint4 g_csum[2 * 8 * 16 * 6];
__device__ uint4 g_halo[128 * 14 * 32];
__device__ unsigned g_flags[FL_COUNT * 8];

struct alignas(64) Maps {
  CUtensorMap x, wqkv_m, wqkv_r, w1_m, w1_r, wo_m, wo_r, w2_m, w2_r, o, h_ml, h_rl, h_st, h_st32, cs_q, cs_1, xs, o_st, x32, out64, out32;
};

__device__ __forceinline__ uint32_t smem_u32(const void* p) { return (uint32_t)__cvta_generic_to_shared(p); }
__device__ __forceinline__ void mbar_init(uint32_t bar, uint32_t cnt) {
  asm volatile("mbarrier.init.shared::cta.b64 [%0], %1;" ::"r"(bar), "r"(cnt) : "memory");
}
__device__ __forceinline__ void mbar_expect_tx(uint32_t bar, uint32_t bytes) {
  asm volatile("mbarrier.arrive.expect_tx.shared::cta.b64 _, [%0], %1;" ::"r"(bar), "r"(bytes) : "memory");
}
__device__ __forceinline__ void mbar_arrive(uint32_t bar) {
  asm volatile("mbarrier.arrive.shared::cta.b64 _, [%0];" ::"r"(bar) : "memory");
}
__device__ __forceinline__ void mbar_wait(uint32_t bar, uint32_t parity) {
  asm volatile("{\n.reg .pred p;\n.reg .u32 c;\nmov.u32 c, 0;\n"
               "WAIT_LOOP:\nmbarrier.try_wait.parity.shared::cta.b64 p, [%0], %1;\n@p bra WAIT_DONE;\n"
               "add.u32 c, c, 1;\nsetp.lt.u32 p, c, 0x1000000;\n@p bra WAIT_LOOP;\ntrap;\nWAIT_DONE:\n}"
               ::"r"(bar), "r"(parity) : "memory");
}
__device__ __forceinline__ unsigned ld_relaxed(const unsigned* p) {
  unsigned v;
  asm volatile("ld.relaxed.gpu.global.u32 %0, [%1];" : "=r"(v) : "l"(p) : "memory");
  return v;
}
__device__ __forceinline__ void flag_poll(int idx, unsigned target) {
  const unsigned* p = &g_flags[idx * 8];
  uint32_t spins = 0;
  while ((int)(ld_relaxed(p) - target) < 0) {
    __nanosleep(20);
    if (++spins > (1u << 22)) __trap();
  }
}
__device__ __forceinline__ void flag_release(int idx) {
  asm volatile("fence.acq_rel.gpu;\nfence.proxy.async;\nred.relaxed.gpu.global.add.u32 [%0], 1;" ::"l"(&g_flags[idx * 8]) : "memory");
}
__device__ __forceinline__ void flag_add(int idx) {
  asm volatile("red.relaxed.gpu.global.add.u32 [%0], 1;" ::"l"(&g_flags[idx * 8]) : "memory");
}
__device__ __forceinline__ void st_b128(uint4* p, uint32_t a, uint32_t b, uint32_t c, uint32_t d) {
  asm volatile("{\n.reg .b128 v;\n.reg .b64 lo, hi;\nmov.b64 lo, {%1, %2};\nmov.b64 hi, {%3, %4};\nmov.b128 v, {lo, hi};\n"
               "st.relaxed.gpu.global.b128 [%0], v;\n}" ::"l"(p), "r"(a), "r"(b), "r"(c), "r"(d) : "memory");
}
__device__ __forceinline__ uint4 ld_b128(const uint4* p) {
  uint4 r;
  asm volatile("{\n.reg .b128 v;\n.reg .b64 lo, hi;\nld.relaxed.gpu.global.b128 v, [%4];\nmov.b128 {lo, hi}, v;\n"
               "mov.b64 {%0, %1}, lo;\nmov.b64 {%2, %3}, hi;\n}"
               : "=r"(r.x), "=r"(r.y), "=r"(r.z), "=r"(r.w) : "l"(p) : "memory");
  return r;
}
__device__ __forceinline__ uint4 ll_wait(const uint4* p, uint32_t tag, uint32_t mask = 0xffffffffu) {
  uint4 v = ld_b128(p);
  uint32_t spins = 0;
  while (!__all_sync(mask, v.w == tag)) {
    __nanosleep(20);
    v = ld_b128(p);
    if (++spins > (1u << 22)) __trap();
  }
  return v;
}
__device__ __forceinline__ void fence_async_all() { asm volatile("fence.proxy.async;" ::: "memory"); }
__device__ __forceinline__ void fence_async_smem() { asm volatile("fence.proxy.async.shared::cta;" ::: "memory"); }

__device__ __forceinline__ void tma2d(uint32_t dst, const CUtensorMap* m, int c0, int c1, uint32_t bar) {
  asm volatile("cp.async.bulk.tensor.2d.shared::cluster.global.mbarrier::complete_tx::bytes [%0], [%1, {%3, %4}], [%2];"
               ::"r"(dst), "l"(m), "r"(bar), "r"(c0), "r"(c1) : "memory");
}
__device__ __forceinline__ void tma3d(uint32_t dst, const CUtensorMap* m, int c0, int c1, int c2, uint32_t bar) {
  asm volatile("cp.async.bulk.tensor.3d.shared::cluster.global.mbarrier::complete_tx::bytes [%0], [%1, {%3, %4, %5}], [%2];"
               ::"r"(dst), "l"(m), "r"(bar), "r"(c0), "r"(c1), "r"(c2) : "memory");
}
__device__ __forceinline__ void tma2d_mc(uint32_t dst, const CUtensorMap* m, int c0, int c1, uint32_t bar) {
  asm volatile("cp.async.bulk.tensor.2d.shared::cluster.global.mbarrier::complete_tx::bytes.multicast::cluster [%0], [%1, {%3, %4}], [%2], %5;"
               ::"r"(dst), "l"(m), "r"(bar), "r"(c0), "r"(c1), "h"((uint16_t)3) : "memory");
}
__device__ __forceinline__ void tma3d_mc(uint32_t dst, const CUtensorMap* m, int c0, int c1, int c2, uint32_t bar) {
  asm volatile("cp.async.bulk.tensor.3d.shared::cluster.global.mbarrier::complete_tx::bytes.multicast::cluster [%0], [%1, {%3, %4, %5}], [%2], %6;"
               ::"r"(dst), "l"(m), "r"(bar), "r"(c0), "r"(c1), "r"(c2), "h"((uint16_t)3) : "memory");
}
__device__ __forceinline__ void mbar_arrive_cluster(uint32_t bar, uint32_t rank) {
  asm volatile("{\n.reg .b32 ra;\nmapa.shared::cluster.u32 ra, %0, %1;\nmbarrier.arrive.shared::cluster.b64 _, [ra];\n}"
               ::"r"(bar), "r"(rank) : "memory");
}
__device__ __forceinline__ void cluster_wait() { asm volatile("barrier.cluster.wait.acquire;" ::: "memory"); }
__device__ __forceinline__ void cluster_sync_tail() {
  asm volatile("barrier.cluster.arrive.relaxed.aligned;\nbarrier.cluster.wait.aligned;" ::: "memory");
}
__device__ __forceinline__ void cluster_sync() {
  asm volatile("barrier.cluster.arrive.release.aligned;\nbarrier.cluster.wait.acquire.aligned;" ::: "memory");
}
struct FSlice { int a0, r0; bool wide; };
__device__ __forceinline__ FSlice f_slice(int j) {
  const int s32 = (int)((0x2F28221B140D0600ull >> (8 * j)) & 0xFF);
  FSlice f;
  f.a0 = 32 * (s32 + (s32 & 1));
  f.r0 = (s32 & 1) ? 32 * s32 : 32 * s32 + 192;
  f.wide = (j != 0) && (j != 5);
  return f;
}
__device__ __forceinline__ void tma2d_store(const CUtensorMap* m, int c0, int c1, uint32_t src) {
  asm volatile("cp.async.bulk.tensor.2d.global.shared::cta.bulk_group [%0, {%2, %3}], [%1];"
               ::"l"(m), "r"(src), "r"(c0), "r"(c1) : "memory");
}
__device__ __forceinline__ void tma3d_store(const CUtensorMap* m, int c0, int c1, int c2, uint32_t src) {
  asm volatile("cp.async.bulk.tensor.3d.global.shared::cta.bulk_group [%0, {%2, %3, %4}], [%1];"
               ::"l"(m), "r"(src), "r"(c0), "r"(c1), "r"(c2) : "memory");
}
__device__ __forceinline__ void tma2d_add(const CUtensorMap* m, int c0, int c1, uint32_t src) {
  asm volatile("cp.reduce.async.bulk.tensor.2d.global.shared::cta.add.tile.bulk_group [%0, {%2, %3}], [%1];"
               ::"l"(m), "r"(src), "r"(c0), "r"(c1) : "memory");
}
__device__ __forceinline__ void prefetch_map(const CUtensorMap* m) {
  asm volatile("prefetch.tensormap [%0];" ::"l"(m) : "memory");
}
__device__ __forceinline__ void l2_prefetch(const void* p, uint32_t bytes) {
  asm volatile("cp.async.bulk.prefetch.L2.global [%0], %1;" ::"l"(p), "r"(bytes) : "memory");
}

__host__ __device__ constexpr uint32_t dlo(uint32_t off, uint32_t lbo) { return (off >> 4) + ((lbo >> 4) << 16); }
__host__ __device__ constexpr uint32_t dhi(uint32_t sbo, uint32_t mode) { return (sbo >> 4) | (mode << 30); }
constexpr uint32_t HI128 = dhi(1024, 1), HI64 = dhi(512, 2), HI32 = dhi(256, 3);
__device__ __forceinline__ void wg_fence() { asm volatile("wgmma.fence.sync.aligned;" ::: "memory"); }
__device__ __forceinline__ void wg_commit() { asm volatile("wgmma.commit_group.sync.aligned;" ::: "memory"); }
template <int N> __device__ __forceinline__ void wg_wait() {
  asm volatile("wgmma.wait_group.sync.aligned %0;" ::"n"(N) : "memory");
}
template <int T> __device__ __forceinline__ void fence_regs(float (&d)[T]) {
#pragma unroll
  for (int i = 0; i < T; i++) asm volatile("" : "+f"(d[i])::"memory");
}

template <int O, uint32_t AOFF, uint32_t AHI, uint32_t BOFF, uint32_t BHI, int T>
__device__ __forceinline__ void wgmma_n192(float (&d)[T], uint32_t abase, uint32_t bbase, int sc) {
  asm volatile("{\n.reg .pred p;\n.reg .b32 lo;\n.reg .b64 da, db;\n"
    "add.u32 lo, %96, %98;\nmov.b64 da, {lo, %99};\n"
    "add.u32 lo, %97, %100;\nmov.b64 db, {lo, %101};\n"
    "setp.ne.b32 p, %102, 0;\n"
    "wgmma.mma_async.sync.aligned.m64n192k16.f32.bf16.bf16 "
    "{%0, %1, %2, %3, %4, %5, %6, %7, %8, %9, %10, %11, %12, %13, %14, %15, %16, %17, %18, %19, %20, %21, %22, %23, %24, %25, %26, %27, %28, %29, %30, %31, %32, %33, %34, %35, %36, %37, %38, %39, %40, %41, %42, %43, %44, %45, %46, %47, %48, %49, %50, %51, %52, %53, %54, %55, %56, %57, %58, %59, %60, %61, %62, %63, %64, %65, %66, %67, %68, %69, %70, %71, %72, %73, %74, %75, %76, %77, %78, %79, %80, %81, %82, %83, %84, %85, %86, %87, %88, %89, %90, %91, %92, %93, %94, %95}, da, db, p, 1, 1, 0, 1;\n}\n"
    : "+f"(d[O + 0]), "+f"(d[O + 1]), "+f"(d[O + 2]), "+f"(d[O + 3]), "+f"(d[O + 4]), "+f"(d[O + 5]), "+f"(d[O + 6]), "+f"(d[O + 7]), "+f"(d[O + 8]), "+f"(d[O + 9]), "+f"(d[O + 10]), "+f"(d[O + 11]), "+f"(d[O + 12]), "+f"(d[O + 13]), "+f"(d[O + 14]), "+f"(d[O + 15]), "+f"(d[O + 16]), "+f"(d[O + 17]), "+f"(d[O + 18]), "+f"(d[O + 19]), "+f"(d[O + 20]), "+f"(d[O + 21]), "+f"(d[O + 22]), "+f"(d[O + 23]), "+f"(d[O + 24]), "+f"(d[O + 25]), "+f"(d[O + 26]), "+f"(d[O + 27]), "+f"(d[O + 28]), "+f"(d[O + 29]), "+f"(d[O + 30]), "+f"(d[O + 31]), "+f"(d[O + 32]), "+f"(d[O + 33]), "+f"(d[O + 34]), "+f"(d[O + 35]), "+f"(d[O + 36]), "+f"(d[O + 37]), "+f"(d[O + 38]), "+f"(d[O + 39]), "+f"(d[O + 40]), "+f"(d[O + 41]), "+f"(d[O + 42]), "+f"(d[O + 43]), "+f"(d[O + 44]), "+f"(d[O + 45]), "+f"(d[O + 46]), "+f"(d[O + 47]), "+f"(d[O + 48]), "+f"(d[O + 49]), "+f"(d[O + 50]), "+f"(d[O + 51]), "+f"(d[O + 52]), "+f"(d[O + 53]), "+f"(d[O + 54]), "+f"(d[O + 55]), "+f"(d[O + 56]), "+f"(d[O + 57]), "+f"(d[O + 58]), "+f"(d[O + 59]), "+f"(d[O + 60]), "+f"(d[O + 61]), "+f"(d[O + 62]), "+f"(d[O + 63]), "+f"(d[O + 64]), "+f"(d[O + 65]), "+f"(d[O + 66]), "+f"(d[O + 67]), "+f"(d[O + 68]), "+f"(d[O + 69]), "+f"(d[O + 70]), "+f"(d[O + 71]), "+f"(d[O + 72]), "+f"(d[O + 73]), "+f"(d[O + 74]), "+f"(d[O + 75]), "+f"(d[O + 76]), "+f"(d[O + 77]), "+f"(d[O + 78]), "+f"(d[O + 79]), "+f"(d[O + 80]), "+f"(d[O + 81]), "+f"(d[O + 82]), "+f"(d[O + 83]), "+f"(d[O + 84]), "+f"(d[O + 85]), "+f"(d[O + 86]), "+f"(d[O + 87]), "+f"(d[O + 88]), "+f"(d[O + 89]), "+f"(d[O + 90]), "+f"(d[O + 91]), "+f"(d[O + 92]), "+f"(d[O + 93]), "+f"(d[O + 94]), "+f"(d[O + 95])
    : "r"(abase), "r"(bbase), "n"(AOFF), "n"(AHI), "n"(BOFF), "n"(BHI), "r"(sc));
}

template <int O, uint32_t AOFF, uint32_t AHI, uint32_t BOFF, uint32_t BHI, int T>
__device__ __forceinline__ void wgmma_n48(float (&d)[T], uint32_t abase, uint32_t bbase, int sc) {
  asm volatile("{\n.reg .pred p;\n.reg .b32 lo;\n.reg .b64 da, db;\n"
    "add.u32 lo, %24, %26;\nmov.b64 da, {lo, %27};\n"
    "add.u32 lo, %25, %28;\nmov.b64 db, {lo, %29};\n"
    "setp.ne.b32 p, %30, 0;\n"
    "wgmma.mma_async.sync.aligned.m64n48k16.f32.bf16.bf16 "
    "{%0, %1, %2, %3, %4, %5, %6, %7, %8, %9, %10, %11, %12, %13, %14, %15, %16, %17, %18, %19, %20, %21, %22, %23}, da, db, p, 1, 1, 0, 1;\n}\n"
    : "+f"(d[O + 0]), "+f"(d[O + 1]), "+f"(d[O + 2]), "+f"(d[O + 3]), "+f"(d[O + 4]), "+f"(d[O + 5]), "+f"(d[O + 6]), "+f"(d[O + 7]), "+f"(d[O + 8]), "+f"(d[O + 9]), "+f"(d[O + 10]), "+f"(d[O + 11]), "+f"(d[O + 12]), "+f"(d[O + 13]), "+f"(d[O + 14]), "+f"(d[O + 15]), "+f"(d[O + 16]), "+f"(d[O + 17]), "+f"(d[O + 18]), "+f"(d[O + 19]), "+f"(d[O + 20]), "+f"(d[O + 21]), "+f"(d[O + 22]), "+f"(d[O + 23])
    : "r"(abase), "r"(bbase), "n"(AOFF), "n"(AHI), "n"(BOFF), "n"(BHI), "r"(sc));
}

template <int O, uint32_t AOFF, uint32_t AHI, uint32_t BOFF, uint32_t BHI, int T>
__device__ __forceinline__ void wgmma_n224(float (&d)[T], uint32_t abase, uint32_t bbase, int sc) {
  asm volatile("{\n.reg .pred p;\n.reg .b32 lo;\n.reg .b64 da, db;\n"
    "add.u32 lo, %112, %114;\nmov.b64 da, {lo, %115};\n"
    "add.u32 lo, %113, %116;\nmov.b64 db, {lo, %117};\n"
    "setp.ne.b32 p, %118, 0;\n"
    "wgmma.mma_async.sync.aligned.m64n224k16.f32.bf16.bf16 "
    "{%0, %1, %2, %3, %4, %5, %6, %7, %8, %9, %10, %11, %12, %13, %14, %15, %16, %17, %18, %19, %20, %21, %22, %23, %24, %25, %26, %27, %28, %29, %30, %31, %32, %33, %34, %35, %36, %37, %38, %39, %40, %41, %42, %43, %44, %45, %46, %47, %48, %49, %50, %51, %52, %53, %54, %55, %56, %57, %58, %59, %60, %61, %62, %63, %64, %65, %66, %67, %68, %69, %70, %71, %72, %73, %74, %75, %76, %77, %78, %79, %80, %81, %82, %83, %84, %85, %86, %87, %88, %89, %90, %91, %92, %93, %94, %95, %96, %97, %98, %99, %100, %101, %102, %103, %104, %105, %106, %107, %108, %109, %110, %111}, da, db, p, 1, 1, 0, 1;\n}\n"
    : "+f"(d[O + 0]), "+f"(d[O + 1]), "+f"(d[O + 2]), "+f"(d[O + 3]), "+f"(d[O + 4]), "+f"(d[O + 5]), "+f"(d[O + 6]), "+f"(d[O + 7]), "+f"(d[O + 8]), "+f"(d[O + 9]), "+f"(d[O + 10]), "+f"(d[O + 11]), "+f"(d[O + 12]), "+f"(d[O + 13]), "+f"(d[O + 14]), "+f"(d[O + 15]), "+f"(d[O + 16]), "+f"(d[O + 17]), "+f"(d[O + 18]), "+f"(d[O + 19]), "+f"(d[O + 20]), "+f"(d[O + 21]), "+f"(d[O + 22]), "+f"(d[O + 23]), "+f"(d[O + 24]), "+f"(d[O + 25]), "+f"(d[O + 26]), "+f"(d[O + 27]), "+f"(d[O + 28]), "+f"(d[O + 29]), "+f"(d[O + 30]), "+f"(d[O + 31]), "+f"(d[O + 32]), "+f"(d[O + 33]), "+f"(d[O + 34]), "+f"(d[O + 35]), "+f"(d[O + 36]), "+f"(d[O + 37]), "+f"(d[O + 38]), "+f"(d[O + 39]), "+f"(d[O + 40]), "+f"(d[O + 41]), "+f"(d[O + 42]), "+f"(d[O + 43]), "+f"(d[O + 44]), "+f"(d[O + 45]), "+f"(d[O + 46]), "+f"(d[O + 47]), "+f"(d[O + 48]), "+f"(d[O + 49]), "+f"(d[O + 50]), "+f"(d[O + 51]), "+f"(d[O + 52]), "+f"(d[O + 53]), "+f"(d[O + 54]), "+f"(d[O + 55]), "+f"(d[O + 56]), "+f"(d[O + 57]), "+f"(d[O + 58]), "+f"(d[O + 59]), "+f"(d[O + 60]), "+f"(d[O + 61]), "+f"(d[O + 62]), "+f"(d[O + 63]), "+f"(d[O + 64]), "+f"(d[O + 65]), "+f"(d[O + 66]), "+f"(d[O + 67]), "+f"(d[O + 68]), "+f"(d[O + 69]), "+f"(d[O + 70]), "+f"(d[O + 71]), "+f"(d[O + 72]), "+f"(d[O + 73]), "+f"(d[O + 74]), "+f"(d[O + 75]), "+f"(d[O + 76]), "+f"(d[O + 77]), "+f"(d[O + 78]), "+f"(d[O + 79]), "+f"(d[O + 80]), "+f"(d[O + 81]), "+f"(d[O + 82]), "+f"(d[O + 83]), "+f"(d[O + 84]), "+f"(d[O + 85]), "+f"(d[O + 86]), "+f"(d[O + 87]), "+f"(d[O + 88]), "+f"(d[O + 89]), "+f"(d[O + 90]), "+f"(d[O + 91]), "+f"(d[O + 92]), "+f"(d[O + 93]), "+f"(d[O + 94]), "+f"(d[O + 95]), "+f"(d[O + 96]), "+f"(d[O + 97]), "+f"(d[O + 98]), "+f"(d[O + 99]), "+f"(d[O + 100]), "+f"(d[O + 101]), "+f"(d[O + 102]), "+f"(d[O + 103]), "+f"(d[O + 104]), "+f"(d[O + 105]), "+f"(d[O + 106]), "+f"(d[O + 107]), "+f"(d[O + 108]), "+f"(d[O + 109]), "+f"(d[O + 110]), "+f"(d[O + 111])
    : "r"(abase), "r"(bbase), "n"(AOFF), "n"(AHI), "n"(BOFF), "n"(BHI), "r"(sc));
}

template <int O, uint32_t AOFF, uint32_t AHI, uint32_t BOFF, uint32_t BHI, int T>
__device__ __forceinline__ void wgmma_n160(float (&d)[T], uint32_t abase, uint32_t bbase, int sc) {
  asm volatile("{\n.reg .pred p;\n.reg .b32 lo;\n.reg .b64 da, db;\n"
    "add.u32 lo, %80, %82;\nmov.b64 da, {lo, %83};\n"
    "add.u32 lo, %81, %84;\nmov.b64 db, {lo, %85};\n"
    "setp.ne.b32 p, %86, 0;\n"
    "wgmma.mma_async.sync.aligned.m64n160k16.f32.bf16.bf16 "
    "{%0, %1, %2, %3, %4, %5, %6, %7, %8, %9, %10, %11, %12, %13, %14, %15, %16, %17, %18, %19, %20, %21, %22, %23, %24, %25, %26, %27, %28, %29, %30, %31, %32, %33, %34, %35, %36, %37, %38, %39, %40, %41, %42, %43, %44, %45, %46, %47, %48, %49, %50, %51, %52, %53, %54, %55, %56, %57, %58, %59, %60, %61, %62, %63, %64, %65, %66, %67, %68, %69, %70, %71, %72, %73, %74, %75, %76, %77, %78, %79}, da, db, p, 1, 1, 0, 1;\n}\n"
    : "+f"(d[O + 0]), "+f"(d[O + 1]), "+f"(d[O + 2]), "+f"(d[O + 3]), "+f"(d[O + 4]), "+f"(d[O + 5]), "+f"(d[O + 6]), "+f"(d[O + 7]), "+f"(d[O + 8]), "+f"(d[O + 9]), "+f"(d[O + 10]), "+f"(d[O + 11]), "+f"(d[O + 12]), "+f"(d[O + 13]), "+f"(d[O + 14]), "+f"(d[O + 15]), "+f"(d[O + 16]), "+f"(d[O + 17]), "+f"(d[O + 18]), "+f"(d[O + 19]), "+f"(d[O + 20]), "+f"(d[O + 21]), "+f"(d[O + 22]), "+f"(d[O + 23]), "+f"(d[O + 24]), "+f"(d[O + 25]), "+f"(d[O + 26]), "+f"(d[O + 27]), "+f"(d[O + 28]), "+f"(d[O + 29]), "+f"(d[O + 30]), "+f"(d[O + 31]), "+f"(d[O + 32]), "+f"(d[O + 33]), "+f"(d[O + 34]), "+f"(d[O + 35]), "+f"(d[O + 36]), "+f"(d[O + 37]), "+f"(d[O + 38]), "+f"(d[O + 39]), "+f"(d[O + 40]), "+f"(d[O + 41]), "+f"(d[O + 42]), "+f"(d[O + 43]), "+f"(d[O + 44]), "+f"(d[O + 45]), "+f"(d[O + 46]), "+f"(d[O + 47]), "+f"(d[O + 48]), "+f"(d[O + 49]), "+f"(d[O + 50]), "+f"(d[O + 51]), "+f"(d[O + 52]), "+f"(d[O + 53]), "+f"(d[O + 54]), "+f"(d[O + 55]), "+f"(d[O + 56]), "+f"(d[O + 57]), "+f"(d[O + 58]), "+f"(d[O + 59]), "+f"(d[O + 60]), "+f"(d[O + 61]), "+f"(d[O + 62]), "+f"(d[O + 63]), "+f"(d[O + 64]), "+f"(d[O + 65]), "+f"(d[O + 66]), "+f"(d[O + 67]), "+f"(d[O + 68]), "+f"(d[O + 69]), "+f"(d[O + 70]), "+f"(d[O + 71]), "+f"(d[O + 72]), "+f"(d[O + 73]), "+f"(d[O + 74]), "+f"(d[O + 75]), "+f"(d[O + 76]), "+f"(d[O + 77]), "+f"(d[O + 78]), "+f"(d[O + 79])
    : "r"(abase), "r"(bbase), "n"(AOFF), "n"(AHI), "n"(BOFF), "n"(BHI), "r"(sc));
}

__device__ __forceinline__ uint32_t pack_bf16(float lo, float hi) {
  uint32_t r;
  asm("cvt.rn.bf16x2.f32 %0, %1, %2;" : "=r"(r) : "f"(hi), "f"(lo));
  return r;
}
__device__ __forceinline__ float bf_lo(uint32_t v) { return __uint_as_float(v << 16); }
__device__ __forceinline__ float bf_hi(uint32_t v) { return __uint_as_float(v & 0xFFFF0000u); }
__device__ __forceinline__ void stsm4(uint32_t addr, uint32_t r0, uint32_t r1, uint32_t r2, uint32_t r3) {
  asm volatile("stmatrix.sync.aligned.m8n8.x4.shared.b16 [%0], {%1, %2, %3, %4};"
               ::"r"(addr), "r"(r0), "r"(r1), "r"(r2), "r"(r3) : "memory");
}
__device__ __forceinline__ void ldsm4(uint32_t (&r)[4], uint32_t addr) {
  asm volatile("ldmatrix.sync.aligned.m8n8.x4.shared.b16 {%0, %1, %2, %3}, [%4];"
               : "=r"(r[0]), "=r"(r[1]), "=r"(r[2]), "=r"(r[3]) : "r"(addr) : "memory");
}
__device__ __forceinline__ void ldsm4t(uint32_t (&r)[4], uint32_t addr) {
  asm volatile("ldmatrix.sync.aligned.m8n8.x4.trans.shared.b16 {%0, %1, %2, %3}, [%4];"
               : "=r"(r[0]), "=r"(r[1]), "=r"(r[2]), "=r"(r[3]) : "r"(addr) : "memory");
}
__device__ __forceinline__ void mma16816(float (&c)[4], uint32_t a0, uint32_t a1, uint32_t a2, uint32_t a3,
                                         uint32_t b0, uint32_t b1) {
  asm volatile("mma.sync.aligned.m16n8k16.row.col.f32.bf16.bf16.f32 {%0,%1,%2,%3}, {%4,%5,%6,%7}, {%8,%9}, {%0,%1,%2,%3};"
               : "+f"(c[0]), "+f"(c[1]), "+f"(c[2]), "+f"(c[3])
               : "r"(a0), "r"(a1), "r"(a2), "r"(a3), "r"(b0), "r"(b1));
}
__device__ __forceinline__ void mma16816_z(float (&c)[4], uint32_t a0, uint32_t a1, uint32_t a2, uint32_t a3,
                                           uint32_t b0, uint32_t b1) {
  asm volatile("mma.sync.aligned.m16n8k16.row.col.f32.bf16.bf16.f32 {%0,%1,%2,%3}, {%4,%5,%6,%7}, {%8,%9}, {%10,%10,%10,%10};"
               : "=f"(c[0]), "=f"(c[1]), "=f"(c[2]), "=f"(c[3])
               : "r"(a0), "r"(a1), "r"(a2), "r"(a3), "r"(b0), "r"(b1), "f"(0.f));
}
__device__ __forceinline__ void mma1688(float (&c)[4], uint32_t a0, uint32_t a1, uint32_t b0) {
  asm volatile("mma.sync.aligned.m16n8k8.row.col.f32.bf16.bf16.f32 {%0,%1,%2,%3}, {%4,%5}, {%6}, {%0,%1,%2,%3};"
               : "+f"(c[0]), "+f"(c[1]), "+f"(c[2]), "+f"(c[3])
               : "r"(a0), "r"(a1), "r"(b0));
}
__device__ __forceinline__ float ex2(float x) {
  float y;
  asm("ex2.approx.ftz.f32 %0, %1;" : "=f"(y) : "f"(x));
  return y;
}
__device__ __forceinline__ float tanh_fast(float x) {
  float y;
  asm("tanh.approx.f32 %0, %1;" : "=f"(y) : "f"(x));
  return y;
}
__device__ __forceinline__ float2 lds64f(uint32_t addr) {
  float2 v;
  asm volatile("ld.shared.v2.f32 {%0, %1}, [%2];" : "=f"(v.x), "=f"(v.y) : "r"(addr));
  return v;
}

#define PROF(slot)
#define PROFW(slot)
#define GT(slot)
#define INTRA(k)
#define INTRAN()
#define STEPT(k)
#define LAT(k, e)
#define TBEG()
#define TEND(var)

struct Attn {
  float s[2][4][4];
  uint32_t p[2][4][2];
  float ilo[2], ihi[2];
};
template <int H> struct HeadTile { static constexpr int T0 = (H == 0) ? 0 : (H == 1) ? 2 : (H == 2) ? 5 : 7; };

template <int H>
__device__ __forceinline__ void attn_scores(Attn& st, const uint32_t (&qp)[10][2], uint32_t kv, int tq) {
  constexpr int T0 = HeadTile<H>::T0;
  uint32_t kb[5][4];
#pragma unroll
  for (int dt = 0; dt < 5; dt++) ldsm4(kb[dt], kv + (T0 + dt) * 16);
  const uint32_t sa0 = tq < 2 ? qp[T0 + 2][0] : 0u, sa1 = tq < 2 ? qp[T0 + 2][1] : 0u;
  const uint32_t sb0 = tq < 2 ? 0u : qp[T0 + 2][0], sb1 = tq < 2 ? 0u : qp[T0 + 2][1];
#pragma unroll
  for (int kt = 0; kt < 4; kt++) {
    mma16816_z(st.s[0][kt], qp[T0][0], qp[T0][1], qp[T0 + 1][0], qp[T0 + 1][1], kb[0][kt], kb[1][kt]);
    mma16816_z(st.s[1][kt], qp[T0 + 3][0], qp[T0 + 3][1], qp[T0 + 4][0], qp[T0 + 4][1], kb[3][kt], kb[4][kt]);
  }
#pragma unroll
  for (int kt = 0; kt < 4; kt++) {
    mma1688(st.s[0][kt], sa0, sa1, kb[2][kt]);
    mma1688(st.s[1][kt], sb0, sb1, kb[2][kt]);
  }
}

__device__ __forceinline__ void attn_softmax(Attn& st, uint32_t vmask, int e) {
  float lo[2][4], hi[2][4], mlo[2], mhi[2], slo[2], shi[2];
  const float ninf = __int_as_float(0xff800000);
#pragma unroll
  for (int h = 0; h < 2; h++) {
#pragma unroll
    for (int kt = 0; kt < 4; kt++) {
      const float vlo = e ? st.s[h][kt][1] : st.s[h][kt][0];
      const float vhi = e ? st.s[h][kt][3] : st.s[h][kt][2];
      lo[h][kt] = ((vmask >> kt) & 1) ? vlo : ninf;
      hi[h][kt] = ((vmask >> (4 + kt)) & 1) ? vhi : ninf;
    }
    mlo[h] = fmaxf(fmaxf(lo[h][0], lo[h][1]), fmaxf(lo[h][2], lo[h][3]));
    mhi[h] = fmaxf(fmaxf(hi[h][0], hi[h][1]), fmaxf(hi[h][2], hi[h][3]));
  }
#pragma unroll
  for (int o = 1; o <= 2; o <<= 1)
#pragma unroll
    for (int h = 0; h < 2; h++) {
      mlo[h] = fmaxf(mlo[h], __shfl_xor_sync(0xffffffffu, mlo[h], o));
      mhi[h] = fmaxf(mhi[h], __shfl_xor_sync(0xffffffffu, mhi[h], o));
    }
  const uint32_t sel0 = e ? 0x1044 : 0x4410, sel1 = e ? 0x3244 : 0x4432;
#pragma unroll
  for (int h = 0; h < 2; h++) {
    slo[h] = 0.f; shi[h] = 0.f;
#pragma unroll
    for (int kt = 0; kt < 4; kt++) {
      const float pl = ex2(lo[h][kt] - mlo[h]), ph = ex2(hi[h][kt] - mhi[h]);
      slo[h] += pl; shi[h] += ph;
      const uint32_t pk = pack_bf16(pl, ph);
      st.p[h][kt][0] = __byte_perm(pk, 0, sel0);
      st.p[h][kt][1] = __byte_perm(pk, 0, sel1);
    }
  }
#pragma unroll
  for (int o = 1; o <= 2; o <<= 1)
#pragma unroll
    for (int h = 0; h < 2; h++) {
      slo[h] += __shfl_xor_sync(0xffffffffu, slo[h], o);
      shi[h] += __shfl_xor_sync(0xffffffffu, shi[h], o);
    }
#pragma unroll
  for (int h = 0; h < 2; h++) { st.ilo[h] = __fdividef(1.f, slo[h]); st.ihi[h] = __fdividef(1.f, shi[h]); }
}

template <int H>
__device__ __forceinline__ void attn_values(const Attn& st, uint32_t (&op)[10][2], uint32_t kv, int tq) {
  constexpr int T0 = HeadTile<H>::T0;
  uint32_t vb[5][4];
#pragma unroll
  for (int dt = 0; dt < 5; dt++) ldsm4t(vb[dt], kv + 160 + (T0 + dt) * 16);
  float o[2][3][4];
#pragma unroll
  for (int h = 0; h < 2; h++)
#pragma unroll
    for (int dt = 0; dt < 3; dt++)
      mma16816_z(o[h][dt], st.p[h][0][0], st.p[h][0][1], st.p[h][1][0], st.p[h][1][1], vb[2 * h + dt][0], vb[2 * h + dt][1]);
#pragma unroll
  for (int h = 0; h < 2; h++)
#pragma unroll
    for (int dt = 0; dt < 3; dt++)
      mma16816(o[h][dt], st.p[h][2][0], st.p[h][2][1], st.p[h][3][0], st.p[h][3][1], vb[2 * h + dt][2], vb[2 * h + dt][3]);
#pragma unroll
  for (int t = 0; t < 5; t++) {
    const int h = t < 2 ? 0 : 1, dt = t < 2 ? t : t - 2;
    float v0 = o[h][dt][0] * st.ilo[h], v1 = o[h][dt][1] * st.ilo[h], v2 = o[h][dt][2] * st.ihi[h], v3 = o[h][dt][3] * st.ihi[h];
    if (t == 2 && tq < 2) {
      v0 = o[0][2][0] * st.ilo[0]; v1 = o[0][2][1] * st.ilo[0]; v2 = o[0][2][2] * st.ihi[0]; v3 = o[0][2][3] * st.ihi[0];
    }
    op[T0 + t][0] = pack_bf16(v0, v1);
    op[T0 + t][1] = pack_bf16(v2, v3);
  }
}

__device__ __forceinline__ uint32_t h_stage_addr(uint32_t sb, int t, int w, int wq, int lane) {
  const int m = lane >> 3;
  const int row = 16 * wq + (m & 1) * 8 + (lane & 7);
  if (t < 24) {
    const int chunk = (t & 7) + (m >> 1);
    return sb + OFF_STG + (t >> 3) * 16384 + w * 8192 + row * 128 + ((chunk ^ (row & 7)) << 4);
  }
  const int chunk = (t - 24) + (m >> 1);
  return sb + OFF_STG + 49152 + w * 4096 + row * 64 + ((chunk ^ ((row >> 1) & 3)) << 4);
}

__device__ __forceinline__ uint32_t fma2(uint32_t a, uint32_t b, uint32_t c) {
  uint32_t d;
  asm volatile("fma.rn.bf16x2 %0, %1, %2, %3;" : "=r"(d) : "r"(a), "r"(b), "r"(c));
  return d;
}
__device__ __forceinline__ uint32_t mul2(uint32_t a, uint32_t b) {
  uint32_t d;
  asm volatile("mul.rn.bf16x2 %0, %1, %2;" : "=r"(d) : "r"(a), "r"(b));
  return d;
}
__device__ __forceinline__ uint32_t tanh2(uint32_t a) {
  uint32_t d;
  asm volatile("tanh.approx.bf16x2 %0, %1;" : "=r"(d) : "r"(a));
  return d;
}
__device__ __forceinline__ uint32_t gelu2(uint32_t hp) {
  const uint32_t K0 = 0x3FCC3FCCu, K1 = 0x3E923E92u;
  const uint32_t u = mul2(hp, fma2(mul2(hp, hp), K1, K0));
  return fma2(hp, tanh2(u), hp);
}
struct GeluAddr { uint32_t row128, x128, row64, x64, cb; };
struct GeluStage { uint32_t hp[4], u[4]; };
template <int T>
__device__ __forceinline__ void gelu_arg(GeluStage& st, const GeluAddr& a, const uint32_t (&hraw)[56], uint32_t chl,
                                         uint32_t rml, uint32_t chh, uint32_t rmh) {
  const uint32_t K0 = 0x3FCC3FCCu, K1 = 0x3E923E92u;
  uint32_t c0, b0, c1, b1;
  asm volatile("ld.shared.v2.u32 {%0, %1}, [%2];" : "=r"(c0), "=r"(b0) : "r"(a.cb + T * 32));
  asm volatile("ld.shared.v2.u32 {%0, %1}, [%2];" : "=r"(c1), "=r"(b1) : "r"(a.cb + T * 32 + 32));
  st.hp[0] = fma2(hraw[2 * T], chl, fma2(rml, c0, b0));
  st.hp[1] = fma2(hraw[2 * T + 1], chh, fma2(rmh, c0, b0));
  st.hp[2] = fma2(hraw[2 * T + 2], chl, fma2(rml, c1, b1));
  st.hp[3] = fma2(hraw[2 * T + 3], chh, fma2(rmh, c1, b1));
#pragma unroll
  for (int i = 0; i < 4; i++) st.u[i] = mul2(st.hp[i], fma2(mul2(st.hp[i], st.hp[i]), K1, K0));
}
template <int T>
__device__ __forceinline__ void gelu_out(const GeluStage& st, const GeluAddr& a) {
  const uint32_t addr = (T < 24) ? a.row128 + (T >> 3) * 16384 + (a.x128 ^ ((T & 7) << 4)) : a.row64 + (a.x64 ^ ((T - 24) << 4));
  uint32_t r[4];
#pragma unroll
  for (int i = 0; i < 4; i++) r[i] = fma2(st.hp[i], tanh2(st.u[i]), st.hp[i]);
  stsm4(addr, r[0], r[1], r[2], r[3]);
}

template <int I> struct IC { static constexpr int v = I; };

template <int B, int E, class F> __device__ __forceinline__ void static_for(F&& f) {
  if constexpr (B < E) { f(IC<B>{}); static_for<B + 1, E>(f); }
}

struct Ring {
  uint32_t slot, phase;
  template <uint32_t N> __device__ __forceinline__ void next() {
    if (++slot == N) { slot = 0; phase ^= 1; }
  }
};

__global__ void __launch_bounds__(kThreads, 1)
fused_kernel(const __grid_constant__ Maps maps, const bf16* __restrict__ x, const bf16* __restrict__ wqkv,
             const bf16* __restrict__ wo, const bf16* __restrict__ w1, const bf16* __restrict__ b1,
             const bf16* __restrict__ w2, const bf16* __restrict__ b2, bf16* __restrict__ out) {
  extern __shared__ __align__(1024) uint8_t smem[];
  GT(22);
  const uint32_t sb = smem_u32(smem);
  const int tid = threadIdx.x, lane = tid & 31;
  const int warp = __shfl_sync(0xffffffffu, tid >> 5, 0);
  const int cta = blockIdx.x;
  const int rank = cta & 1, cl = cta >> 1;
  const int tj = cl >> 3, ti = 2 * (cl & 7) + rank;
  const int me = ti * 8 + tj;
  const int nt = tj & 3, kh = tj >> 2;
  auto bar = [&](uint32_t idx) { return sb + OFF_BAR + idx * 8; };

  if (tid == 256) {
    asm volatile("cp.async.bulk.prefetch.tensor.2d.L2.global.tile [%0, {%1, %2}];" ::"l"(&maps.x), "r"(0), "r"(128 * ti) : "memory");
    asm volatile("cp.async.bulk.prefetch.tensor.2d.L2.global.tile [%0, {%1, %2}];" ::"l"(&maps.x), "r"(64), "r"(128 * ti) : "memory");
  }
  if (tid == 288) {
    const int a0 = f_slice(tj).a0;
#pragma unroll
    for (int q = 0; q < 2; q++)
      asm volatile("cp.async.bulk.prefetch.tensor.3d.L2.global.tile [%0, {%1, %2, %3}];"
                   ::"l"(&maps.w1_m), "r"(a0), "r"(32 * q + 16 * rank), "r"(0) : "memory");
    prefetch_map(&maps.w1_r);
  }
  if (lane == 0) {
    if (sb & 1023) __trap();
#pragma unroll
    for (int u = 0; u < 6; u++) {
      const int i = warp * 6 + u;
      const bool eight = (i >= BAR_A_EMPTY && i < BAR_B_FULL) || (i >= BAR_B_EMPTY && i < BAR_B_PEER) ||
                         (i >= BAR_B2_EMPTY && i < BAR_B2_PEER) || i == BAR_PROL || i == BAR_PROL2 || i == BAR_KV ||
                         i == BAR_O_W || i == BAR_ATT || i == BAR_XROWS || i == BAR_HDONE || i == BAR_H_ST0;
      mbar_init(bar(i), eight ? 8 : 1);
    }
    asm volatile("fence.mbarrier_init.release.cluster;" ::: "memory");
    fence_async_smem();
  }
  __syncthreads();
  asm volatile("barrier.cluster.arrive.relaxed.aligned;" ::: "memory");
  const FSlice fs = f_slice(tj);
  const bool jodd = tj & 1, nodd = nt & 1;
  const int qmain = 80 * tj + (jodd ? 16 : 0), qrem = 80 * tj + (jodd ? 0 : 64);
  const int omain = 160 * nt + (nodd ? 32 : 0), orem = 160 * nt + (nodd ? 0 : 128);

  if (warp >= 8) {
    asm volatile("setmaxnreg.dec.sync.aligned.u32 40;");
    if (warp == 8) {
      if (lane == 0) {
        PROF(0);
        Ring r{0, 1};
#pragma unroll 1
        for (int it = 0; it < 20; it++) {
          mbar_wait(bar(BAR_A_EMPTY + r.slot), r.phase);
          mbar_expect_tx(bar(BAR_A_FULL + r.slot), 16384);
          tma2d(sb + OFF_A + r.slot * A_SLOT, &maps.x, 64 * (it < 10 ? it : it - 10), 128 * ti, bar(BAR_A_FULL + r.slot));
          r.next<A_N>();
        }
        mbar_wait(bar(BAR_H_RDY), 0);
        PROF(2);
#pragma unroll 1
        for (int s = 0; s < 4; s++) {
          const FSlice f2 = f_slice(4 * kh + s);
#pragma unroll 1
          for (int t = 0; t < (f2.wide ? 4 : 3); t++) {
            mbar_wait(bar(BAR_A_EMPTY + r.slot), r.phase);
            const uint32_t dst = sb + OFF_A + r.slot * A_SLOT, fb = bar(BAR_A_FULL + r.slot);
            if (t < 3) {
              mbar_expect_tx(fb, 16384);
              tma2d(dst, &maps.h_ml, f2.a0 + 64 * t, 128 * ti, fb);
            } else {
              mbar_expect_tx(fb, 8192);
              tma2d(dst, &maps.h_rl, f2.r0, 128 * ti, fb);
            }
            r.next<A_N>();
          }
        }
        mbar_wait(bar(BAR_O_RDY), 0);
        PROF(1);
#pragma unroll 1
        for (int t = 0; t < 5; t++) {
          mbar_wait(bar(BAR_A_EMPTY + r.slot), r.phase);
          const uint32_t fb = bar(BAR_A_FULL + r.slot);
          mbar_expect_tx(fb, 16384);
          tma2d(sb + OFF_A + r.slot * A_SLOT, &maps.o, 320 * kh + 64 * t, 128 * ti, fb);
          r.next<A_N>();
        }
      }
    } else if (warp == 9) {
      if (lane == 0) {
        cluster_wait();
        Ring r{0, 1};
        const uint32_t half = sb + OFF_B + rank * 8192;
        const int k16 = 16 * rank;
        auto wait_free = [&]() {
          mbar_wait(bar(BAR_B_EMPTY + r.slot), r.phase);
          mbar_wait(bar(BAR_B_PEER + r.slot), r.phase);
        };
#pragma unroll 1
        for (int q = 0; q < 20; q++) {
          wait_free();
          LAT(2, q);
          const uint32_t dst = half + r.slot * B_SLOT, fb = bar(BAR_B_FULL + r.slot);
          mbar_expect_tx(fb, fs.wide ? 14336 : 12288);
          tma3d_mc(dst, &maps.w1_m, fs.a0, 32 * q + k16, 0, fb);
          if (fs.wide) tma2d_mc(dst + 6144, &maps.w1_r, fs.r0, 32 * q + k16, fb);
          r.next<B_N>();
          if (q == 8) {
            l2_prefetch((const char*)wo + cta * 6400, 6400);
            l2_prefetch((const char*)w2 + cta * 17280, 17280);
          }
        }
#pragma unroll 1
        for (int q = 0; q < 20; q++) {
          wait_free();
          LAT(2, 20 + q);
          const uint32_t dst = half + r.slot * B_SLOT, fb = bar(BAR_B_FULL + r.slot);
          mbar_expect_tx(fb, 15360);
          tma3d_mc(dst, &maps.wqkv_m, qmain, 32 * q + k16, 0, fb);
          tma3d_mc(dst + 6144, &maps.wqkv_r, qrem, 32 * q + k16, 0, fb);
          r.next<B_N>();
        }
        const uint32_t half2 = sb + OFF_B + rank * 6144;
        int s2 = 0, q2 = 0;
        FSlice f2 = f_slice(4 * kh);
#pragma unroll 1
        for (int u = 0; u < B2_STEPS; u++) {
          if (u < 7 && u != 1 && u != 5) {
            wait_free();
            r.next<B_N>();
            if (u == 0) { wait_free(); r.next<B_N>(); }
          }
          const uint32_t v = u & 7, par = ((u >> 3) & 1) ^ 1;
          mbar_wait(bar(BAR_B2_EMPTY + v), par);
          mbar_wait(bar(BAR_B2_PEER + v), par);
          const uint32_t dst = half2 + ((v + 6) & 7) * B2_SLOT, fb = bar(BAR_B2_FULL + v);
          mbar_expect_tx(fb, 10240);
          if (u < 27) {
            const int krow = (q2 < 6 ? f2.a0 + 32 * q2 : f2.r0) + k16;
            tma3d_mc(dst, &maps.w2_m, omain, krow, 0, fb);
            tma2d_mc(dst + 4096, &maps.w2_r, orem, krow, fb);
            if (++q2 == (f2.wide ? 7 : 6)) { q2 = 0; s2++; f2 = f_slice(4 * kh + (s2 & 3)); }
          } else {
            const int krow = 320 * kh + 32 * (u - 27) + k16;
            tma3d_mc(dst, &maps.wo_m, omain, krow, 0, fb);
            tma2d_mc(dst + 4096, &maps.wo_r, orem, krow, fb);
          }
        }
      }
    } else if (warp == 10) {
      unsigned ep = 0;
      if (lane == 0) {
        ep = *(volatile unsigned*)&g_flags[FL_DONE * 8] / kCtas + 1;
        *(volatile unsigned*)(smem + OFF_EPOCH) = ep;
        mbar_arrive(bar(BAR_EPOCH));
        atomicAdd(&g_flags[FL_DONE * 8], 1u);
        mbar_wait(bar(BAR_A_FULL + 1), 0);
        const bool has1 = ti < (fs.wide ? 14 : 12);
        mbar_expect_tx(bar(BAR_CS_FULL), (has1 ? 20480 : 0) + 20480);
#pragma unroll 1
        for (int q = 0; q < 5; q++) tma2d(sb + OFF_STG + 20480 + q * 4096, &maps.xs, 128 * q, 128 * ti + 16 * tj, bar(BAR_CS_FULL));
        if (has1) {
          const int col = ti < 12 ? fs.a0 + 16 * ti : fs.r0 + 16 * (ti - 12);
#pragma unroll 1
          for (int q = 0; q < 4; q++) tma2d(sb + OFF_STG + q * 5120, &maps.cs_1, col, 160 * q, bar(BAR_CS_FULL));
        }
      }
      ep = __shfl_sync(0xffffffffu, ep, 0);
      uint32_t b2v[4];
#pragma unroll
      for (int u = 0; u < 4; u++) {
        const int i2 = lane + 32 * u;
        const int c = 2 * i2;
        const int col = c < 192 ? fs.a0 + c : fs.r0 + c - 192;
        b2v[u] = (i2 < 112 && (c < 192 || fs.wide)) ? mul2(__ldg((const uint32_t*)(b1 + col)), 0x3F003F00u) : 0u;
      }
      {
#pragma unroll
        for (int u = 0; u < 2; u++) {
          const int i2 = lane + 32 * u, t = i2 >> 2;
          if (i2 < 40) {
            const int col = (t < 6 ? omain + 80 * kh + 8 * t : (kh ? orem : omain + 48) + 8 * (t - 6)) + 2 * (i2 & 3);
            *(uint32_t*)(smem + OFF_B2 + i2 * 4) = __ldg((const uint32_t*)(b2 + col));
          }
        }
      }
      auto publish_sums = [&](int which) {
        const float* red = (const float*)(smem + OFF_RED) + which * 128 + (lane & 15);
        float s = 0.f;
#pragma unroll
        for (int r = 0; r < 8; r++) s += red[r * 16];
        const int l3 = min(3 * lane, 15);
        const float s0 = __shfl_sync(0xffffffffu, s, l3), s1 = __shfl_sync(0xffffffffu, s, min(l3 + 1, 15)),
                    s2 = __shfl_sync(0xffffffffu, s, min(l3 + 2, 15));
        if (lane < 6)
          st_b128(&g_csum[((which * 8 + tj) * 16 + ti) * 6 + lane], __float_as_uint(s0), __float_as_uint(s1),
                  __float_as_uint(s2), ep);
      };
      auto gather_sums = [&](int which, int npiece, float* dst) {
        const uint4* src = &g_csum[(which * 8 + tj) * 16 * 6];
        uint4 v[3];
        uint32_t spins = 0;
        while (true) {
          bool ok = true;
#pragma unroll
          for (int u = 0; u < 3; u++) {
            v[u] = ld_b128(src + min(lane + 32 * u, npiece * 6 - 1));
            ok = ok && v[u].w == ep;
          }
          if (__all_sync(0xffffffffu, ok)) break;
          __nanosleep(20);
          if (++spins > (1u << 22)) __trap();
        }
#pragma unroll
        for (int u = 0; u < 3; u++) {
          const int i2 = min(lane + 32 * u, npiece * 6 - 1);
          const int piece = i2 / 6, p = i2 - 6 * piece;
          float* d = dst + 16 * piece + 3 * p;
          d[0] = __uint_as_float(v[u].x);
          if (p < 5) { d[1] = __uint_as_float(v[u].y); d[2] = __uint_as_float(v[u].z); }
        }
        __syncwarp();
      };
      if (lane == 0) {
        mbar_wait(bar(BAR_XROWS), 0);
        if (ti < 15) {
          const int col = ti < 12 ? 640 * (ti >> 2) + qmain + 16 * (ti & 3) : 640 * (ti - 12) + qrem;
          mbar_expect_tx(bar(BAR_CS2_FULL), 20480);
#pragma unroll 1
          for (int q = 0; q < 4; q++) tma2d(sb + OFF_STG + 20480 + q * 5120, &maps.cs_q, col, 160 * q, bar(BAR_CS2_FULL));
        } else {
          mbar_arrive(bar(BAR_CS2_FULL));
        }
      }
      __syncwarp();
      mbar_wait(bar(BAR_PROL), 0);
      publish_sums(0);
      PROF(7);
      {
        float* tmp = (float*)(smem + OFF_C);
        gather_sums(0, 14, tmp);
        PROF(12);
#pragma unroll
        for (int u = 0; u < 4; u++) {
          const int i2 = lane + 32 * u;
          if (i2 < 112) *(uint2*)(smem + OFF_CB + i2 * 8) = make_uint2(pack_bf16(tmp[2 * i2], tmp[2 * i2 + 1]), b2v[u]);
        }
        __syncwarp();
      }
      if (lane == 0) { mbar_arrive(bar(BAR_AUX)); PROF(13); }
      mbar_wait(bar(BAR_PROL2), 0);
      publish_sums(1);
      gather_sums(1, 15, (float*)(smem + OFF_C));
      {
        uint32_t pk[4];
#pragma unroll
        for (int u = 0; u < 4; u++) {
          const int i2 = min(lane + 32 * u, 119);
          const float2 cv = *(const float2*)(smem + OFF_C + i2 * 8);
          pk[u] = pack_bf16(cv.x, cv.y);
        }
#pragma unroll
        for (int u = 0; u < 4; u++)
          if (lane + 32 * u < 120) *(uint32_t*)(smem + OFF_CQ + (lane + 32 * u) * 4) = pk[u];
        __syncwarp();
      }
      if (lane == 0) mbar_arrive(bar(BAR_AUX2));
      {
#pragma unroll 4
        for (int i2 = lane; i2 < 1280; i2 += 32) {
          const int r = i2 / 10, c = i2 - 10 * r;
          const int col = c < 6 ? omain + 80 * kh + 8 * c : (kh ? orem : omain + 48) + 8 * (c - 6);
          __stcg((uint4*)(out + (size_t)(128 * ti + r) * kD + col), make_uint4(0, 0, 0, 0));
        }
        __syncwarp();
        if (lane == 0)
          asm volatile("fence.acq_rel.gpu;\nfence.proxy.async;\nred.relaxed.gpu.global.add.u32 [%0], 1;"
                       ::"l"(&g_flags[(FL_Z + ti * 4 + nt) * 8]) : "memory");
      }
      if (lane == 0) {
        mbar_wait(bar(BAR_H_ST0), 0);
        flag_add(FL_H + ti * 8 + tj);
        PROF(6);
      }
      __syncwarp();
      if (lane < 4) flag_poll(FL_H + ti * 8 + 4 * kh + lane, ep);
      __syncwarp();
      if (lane == 0) {
        mbar_arrive(bar(BAR_H_RDY));
        PROF(3);
        flag_poll(FL_Z + ti * 4 + nt, 2 * ep);
        asm volatile("fence.acq_rel.gpu;\nfence.proxy.async;" ::: "memory");
        mbar_arrive(bar(BAR_ZERO));
      }
      if (lane == 0) {
        mbar_wait(bar(BAR_ATT), 0);
        mbar_expect_tx(bar(BAR_XR), 16384 + 8192);
        tma2d(sb + OFF_XR, &maps.x, omain + 80 * kh, 128 * ti, bar(BAR_XR));
        tma2d(sb + OFF_XR + 16384, &maps.x32, kh ? orem : omain + 48, 128 * ti, bar(BAR_XR));
        mbar_wait(bar(BAR_O_W), 0);
        flag_add(FL_O + ti * 2 + kh);
        PROF(14);
        flag_poll(FL_O + ti * 2 + kh, 4 * ep);
        mbar_arrive(bar(BAR_O_RDY));
        PROF(4);
      }
    } else {
      if (lane >= 1 && lane <= (int)(sizeof(Maps) / sizeof(CUtensorMap))) prefetch_map((const CUtensorMap*)&maps + lane - 1);
      if (lane == 0) {
        cluster_wait();
        Ring r{0, 0};
#pragma unroll 1
        for (int e = 0; e < 40; e++) {
          mbar_wait(bar(BAR_B_EMPTY + r.slot), r.phase);
          LAT(0, e);
          mbar_arrive_cluster(bar(BAR_B_PEER + r.slot), rank ^ 1);
          r.next<B_N>();
        }
#pragma unroll 1
        for (int e = 0; e < B2_STEPS - (int)B2_N; e++) {
          mbar_wait(bar(BAR_B2_EMPTY + (e & 7)), (e >> 3) & 1);
          mbar_arrive_cluster(bar(BAR_B2_PEER + (e & 7)), rank ^ 1);
        }
      }
    }
  } else {
    asm volatile("setmaxnreg.inc.sync.aligned.u32 232;");
    const int w = warp >> 2, wq = warp & 3;
    const int g = lane >> 2, tq = lane & 3;
    PROFW(0);
    GT(20);

    const int row_lo = 128 * ti + 64 * w + 16 * wq + g;
    const uint32_t d0 = (sb & 0x3FFFF) >> 4;
    const uint32_t d128 = d0 + w * (8192 >> 4);
    const uint32_t d64 = d0 + w * (4096 >> 4);

    Ring ra{0, 0}, rb{0, 0};
    uint32_t prev_a = 0, prev_b = 0;
    auto wait_a = [&]() {
      mbar_wait(bar(BAR_A_FULL + ra.slot), ra.phase);
    };
    auto wait_b = [&]() {
      mbar_wait(bar(BAR_B_FULL + rb.slot), rb.phase);
    };
    auto a_desc = [&]() { return d128 + dlo(OFF_A, 16) + ra.slot * (A_SLOT >> 4); };
    auto b_desc = [&]() { return d0 + (OFF_B >> 4) + rb.slot * (B_SLOT >> 4); };
    auto nop = []() {};
    auto step1 = [&](auto HF, auto&& k0, auto&& k1, bool first, bool last, auto&& hook_a, auto&& hook_b) {
      constexpr int hf = HF.v;
      const uint32_t ad = a_desc(), bd = b_desc();
      const uint32_t cur_a = ra.slot, cur_b = rb.slot;
      STEPT(1);
      INTRA(0);
      __syncwarp();
      wg_fence();
      k0(ad, bd);
      wg_commit();
      rb.next<B_N>();
      if constexpr (hf == 1) ra.next<A_N>();
      wg_wait<1>();
      if (!first && lane == 0) {
        mbar_arrive(bar(BAR_B_EMPTY + prev_b));
        if constexpr (hf == 0) mbar_arrive(bar(BAR_A_EMPTY + prev_a));
      }
      INTRA(1);
      hook_a();
      k1(ad, bd);
      wg_commit();
      INTRA(2);
      if (!last) {
        if constexpr (hf == 1) wait_a();
        wait_b();
      }
      INTRA(3);
      hook_b();
      INTRAN();
      prev_b = cur_b;
      if constexpr (hf == 1) prev_a = cur_a;
    };
    auto drain1 = [&]() {
      wg_wait<0>();
      if (lane == 0) { mbar_arrive(bar(BAR_B_EMPTY + prev_b)); mbar_arrive(bar(BAR_A_EMPTY + prev_a)); }
    };

    unsigned ep = 0;
    uint4 sl = make_uint4(0, 0, 0, 0), sh = sl;
    uint32_t hraw[56];
    {
      float acch[112];
      int sc0 = 0;
      auto step_h = [&](auto HF, bool first, bool last, auto&& hook_a, auto&& hook_b) {
        constexpr int hf = HF.v;
        step1(HF,
              [&](uint32_t ad, uint32_t bd) { wgmma_n224<0, hf * 4, HI128, dlo(0, 2048), HI128>(acch, ad, bd, sc0); sc0 = 1; },
              [&](uint32_t ad, uint32_t bd) { wgmma_n224<0, hf * 4 + 2, HI128, dlo(8192, 2048), HI128>(acch, ad, bd, 1); },
              first, last, hook_a, hook_b);
      };
      float ca[8];
      auto cols_load = [&](auto Q0, auto Q1, uint32_t off) {
        const uint32_t base = sb + OFF_STG + off + tid * 16;
        if constexpr (Q0.v == 0) {
#pragma unroll
          for (int q = 0; q < 8; q++) ca[q] = 0.f;
        }
#pragma unroll
        for (int q = Q0.v; q < Q1.v; q++) {
          uint32_t v0, v1, v2, v3;
          asm volatile("ld.shared.v4.u32 {%0, %1, %2, %3}, [%4];" : "=r"(v0), "=r"(v1), "=r"(v2), "=r"(v3) : "r"(base + q * 4096));
          ca[0] += bf_lo(v0); ca[1] += bf_hi(v0); ca[2] += bf_lo(v1); ca[3] += bf_hi(v1);
          ca[4] += bf_lo(v2); ca[5] += bf_hi(v2); ca[6] += bf_lo(v3); ca[7] += bf_hi(v3);
        }
      };
      auto cols_reduce = [&](int slot) {
        float a4[4], a2[2];
#pragma unroll
        for (int q = 0; q < 4; q++) {
          const float keep = (lane & 2) ? ca[4 + q] : ca[q], send = (lane & 2) ? ca[q] : ca[4 + q];
          a4[q] = keep + __shfl_xor_sync(0xffffffffu, send, 2);
        }
#pragma unroll
        for (int q = 0; q < 2; q++) {
          const float keep = (lane & 4) ? a4[2 + q] : a4[q], send = (lane & 4) ? a4[q] : a4[2 + q];
          a2[q] = keep + __shfl_xor_sync(0xffffffffu, send, 4);
        }
        float a1 = ((lane & 8) ? a2[1] : a2[0]) + __shfl_xor_sync(0xffffffffu, (lane & 8) ? a2[0] : a2[1], 8);
        a1 += __shfl_xor_sync(0xffffffffu, a1, 16);
        const int col = (lane & 1) * 8 + ((lane >> 1) & 1) * 4 + ((lane >> 2) & 1) * 2 + ((lane >> 3) & 1);
        if (lane < 16) ((float*)(smem + OFF_RED))[slot * 128 + warp * 16 + col] = a1;
        __syncwarp();
        if (lane == 0) mbar_arrive(bar(slot ? BAR_PROL2 : BAR_PROL));
      };
      uint32_t xw[2][10];
      float mean[2], ssq[2];
      auto rows_load = [&]() {
#pragma unroll
        for (int r = 0; r < 2; r++)
#pragma unroll
          for (int q = 0; q < 5; q++)
            asm volatile("ld.shared.v2.u32 {%0, %1}, [%2];" : "=r"(xw[r][2 * q]), "=r"(xw[r][2 * q + 1])
                         : "r"(sb + OFF_STG + 20480 + q * 4096 + (2 * warp + r) * 256 + lane * 8));
      };
      auto rows_sum = [&](auto R) {
        constexpr int r = R.v;
        float s[4] = {0.f, 0.f, 0.f, 0.f};
#pragma unroll
        for (int q = 0; q < 10; q++) { s[(2 * q) & 3] += bf_lo(xw[r][q]); s[(2 * q + 1) & 3] += bf_hi(xw[r][q]); }
        mean[r] = (s[0] + s[1]) + (s[2] + s[3]);
      };
      auto rows_reduce = [&](float (&v)[2]) {
#pragma unroll
        for (int o = 16; o > 0; o >>= 1)
#pragma unroll
          for (int r = 0; r < 2; r++) v[r] += __shfl_xor_sync(0xffffffffu, v[r], o);
      };
      auto rows_ssq = [&](auto R) {
        constexpr int r = R.v;
        const float mn = mean[r] * (1.f / kD);
        float s0 = 0.f, s1 = 0.f;
#pragma unroll
        for (int q = 0; q < 10; q++) {
          const float d0v = bf_lo(xw[r][q]) - mn, d1v = bf_hi(xw[r][q]) - mn;
          s0 = fmaf(d0v, d0v, s0); s1 = fmaf(d1v, d1v, s1);
        }
        ssq[r] = s0 + s1;
      };
      auto rows_finish = [&]() {
        const float var = (lane & 1 ? ssq[1] : ssq[0]) * (1.f / kD), mn = (lane & 1 ? mean[1] : mean[0]) * (1.f / kD);
        const float rstd = rsqrtf(var + 1e-5f);
        const float var2 = var * rstd * rstd;
        const float rs = rstd * rsqrtf(var2 + 1e-5f);
        if (lane < 2)
          st_b128(&g_stats[128 * ti + 16 * tj + 2 * warp + lane], __float_as_uint(rstd), __float_as_uint(mn),
                  __float_as_uint(rs), ep);
      };
      wait_a();
      wait_b();
      fence_regs(acch);
      wg_fence();
      step_h(IC<0>{}, true, false, nop, nop);
      step_h(IC<1>{}, false, false, nop, nop);
      PROFW(2);
#pragma unroll 1
      for (int kt = 1; kt < 3; kt++) {
        step_h(IC<0>{}, false, false, nop, nop);
        step_h(IC<1>{}, false, false, nop, nop);
      }
      static_for<6, 20>([&](auto Q) {
        constexpr int q = Q.v;
        step_h(IC<(q & 1)>{}, false, q == 19, nop, [&]() {
          if constexpr (q == 7) {
            mbar_wait(bar(BAR_EPOCH), 0);
            ep = *(volatile unsigned*)(smem + OFF_EPOCH);
            mbar_wait(bar(BAR_CS_FULL), 0);
            rows_load();
            __syncwarp();
            if (lane == 0) mbar_arrive(bar(BAR_XROWS));
            rows_sum(IC<0>{});
          }
          if constexpr (q == 8) { rows_sum(IC<1>{}); rows_reduce(mean); }
          if constexpr (q == 9) rows_ssq(IC<0>{});
          if constexpr (q == 10) rows_ssq(IC<1>{});
          if constexpr (q == 11) { rows_reduce(ssq); rows_finish(); }
          if constexpr (q == 12) cols_load(IC<0>{}, IC<3>{}, 0);
          if constexpr (q == 13) { cols_load(IC<3>{}, IC<5>{}, 0); cols_reduce(0); PROFW(1); }
          if constexpr (q == 15) { mbar_wait(bar(BAR_CS2_FULL), 0); cols_load(IC<0>{}, IC<3>{}, 20480); }
          if constexpr (q == 16) { cols_load(IC<3>{}, IC<5>{}, 20480); cols_reduce(1); }
          if constexpr (q == 17) { sl = ld_b128(&g_stats[row_lo]); sh = ld_b128(&g_stats[row_lo + 8]); }
        });
      });
      cluster_wait();
      drain1();
      fence_regs(acch);
      PROFW(7);
#pragma unroll
      for (int t = 0; t < 28; t++) {
        hraw[2 * t] = pack_bf16(acch[4 * t], acch[4 * t + 1]);
        hraw[2 * t + 1] = pack_bf16(acch[4 * t + 2], acch[4 * t + 3]);
      }
    }

    float2 st_lo, st_hi;
    uint32_t qp[10][2];
    {
      float acc[120];
      int sc0 = 0;
      auto step_q = [&](auto HF, bool first, bool last, auto&& hook_a, auto&& hook_b) {
        constexpr int hf = HF.v;
        step1(HF,
              [&](uint32_t ad, uint32_t bd) {
                wgmma_n192<0, hf * 4, HI128, dlo(0, 2048), HI128>(acc, ad, bd, sc0);
                wgmma_n48<96, hf * 4, HI128, dlo(6144, 512), HI32>(acc, ad, bd, sc0);
                sc0 = 1;
              },
              [&](uint32_t ad, uint32_t bd) {
                wgmma_n192<0, hf * 4 + 2, HI128, dlo(8192, 2048), HI128>(acc, ad, bd, 1);
                wgmma_n48<96, hf * 4 + 2, HI128, dlo(8192 + 6144, 512), HI32>(acc, ad, bd, 1);
              },
              first, last, hook_a, hook_b);
      };
      uint32_t chl = 0, rml = 0, chh = 0, rmh = 0;
      GeluAddr ga;
      {
        const int m = lane >> 3, row = 16 * wq + (m & 1) * 8 + (lane & 7);
        ga.row128 = sb + OFF_STG + w * 8192 + row * 128;
        ga.x128 = ((row & 7) ^ (m >> 1)) << 4;
        ga.row64 = sb + OFF_STG + 49152 + w * 4096 + row * 64;
        ga.x64 = (((row >> 1) & 3) ^ (m >> 1)) << 4;
        ga.cb = sb + OFF_CB + (lane & 3) * 8;
      }
      wait_a();
      wait_b();
      fence_regs(acc);
      wg_fence();
      step_q(IC<0>{}, true, false, nop, nop);
      step_q(IC<1>{}, false, false, nop,
             [&]() {
               uint32_t spins = 0;
               while (!__all_sync(0xffffffffu, sl.w == ep && sh.w == ep)) {
                 sl = ld_b128(&g_stats[row_lo]); sh = ld_b128(&g_stats[row_lo + 8]);
                 if (++spins > (1u << 22)) __trap();
               }
               st_lo = make_float2(__uint_as_float(sl.x), __uint_as_float(sl.x) * __uint_as_float(sl.y));
               st_hi = make_float2(__uint_as_float(sh.x), __uint_as_float(sh.x) * __uint_as_float(sh.y));
               const float hl = 0.5f * __uint_as_float(sl.z), hh = 0.5f * __uint_as_float(sh.z);
               const float ml = -hl * __uint_as_float(sl.y), mh = -hh * __uint_as_float(sh.y);
               chl = pack_bf16(hl, hl); rml = pack_bf16(ml, ml);
               chh = pack_bf16(hh, hh); rmh = pack_bf16(mh, mh);
               mbar_wait(bar(BAR_AUX), 0);
               mbar_wait(bar(BAR_PROL2), 0);
             });
      GeluStage g0, g1;
      static_for<2, 20>([&](auto Q) {
        constexpr int q = Q.v;
        constexpr int n_in = q < 6 ? 2 : q < 12 ? 1 : 0, p_in = q < 6 ? 2 * (q - 2) : q + 2;
        constexpr int n_out = q < 3 ? 0 : q < 7 ? 2 : q < 13 ? 1 : 0, p_out = q < 7 ? 2 * (q - 3) : q + 1;
        step_q(IC<(q & 1)>{}, false, q == 19, nop, [&]() {
          if constexpr (n_out >= 1) gelu_out<2 * p_out>(g0, ga);
          if constexpr (n_out == 2) gelu_out<2 * p_out + 2>(g1, ga);
          if constexpr (n_in >= 1) gelu_arg<2 * p_in>(g0, ga, hraw, chl, rml, chh, rmh);
          if constexpr (n_in == 2) gelu_arg<2 * p_in + 2>(g1, ga, hraw, chl, rml, chh, rmh);
          if constexpr (q == 4 || q == 6 || q == 10 || q == 12) {
            constexpr int T = q == 4 ? 0 : q == 6 ? 1 : q == 10 ? 2 : 3;
            fence_async_smem();
            __syncwarp();
            if (lane == 0) {
              const int row0 = 128 * ti + 64 * w + 16 * wq;
              if constexpr (T < 3) tma2d_store(&maps.h_st, fs.a0 + 64 * T, row0, sb + OFF_STG + T * 16384 + w * 8192 + wq * 2048);
              else if (fs.wide) tma2d_store(&maps.h_st32, fs.r0, row0, sb + OFF_STG + 49152 + w * 4096 + wq * 1024);
              if constexpr (T == 3) asm volatile("cp.async.bulk.commit_group;" ::: "memory");
            }
            if constexpr (T == 3) PROFW(8);
          }
          if constexpr (q == 15) {
            if (lane == 0) {
              asm volatile("cp.async.bulk.wait_group 0;" ::: "memory");
              mbar_arrive(bar(BAR_HDONE));
              mbar_arrive(bar(BAR_H_ST0));
            }
          }
        });
      });
      drain1();
      fence_regs(acc);
      PROFW(3);
      uint32_t qkv[60];
#pragma unroll
      for (int t = 0; t < 30; t++) {
        qkv[2 * t] = pack_bf16(acc[4 * t], acc[4 * t + 1]);
        qkv[2 * t + 1] = pack_bf16(acc[4 * t + 2], acc[4 * t + 3]);
      }
      mbar_wait(bar(BAR_HDONE), 0);
      mbar_wait(bar(BAR_AUX2), 0);
      auto ln_tile = [&](auto T, uint32_t al, uint32_t ml, uint32_t ah, uint32_t mh) {
        constexpr int t = T.v;
        uint32_t c2;
        asm volatile("ld.shared.u32 %0, [%1];" : "=r"(c2) : "r"(sb + OFF_CQ + (t * 4 + tq) * 4));
        qkv[2 * t] = fma2(qkv[2 * t], al, mul2(ml, c2));
        qkv[2 * t + 1] = fma2(qkv[2 * t + 1], ah, mul2(mh, c2));
      };
      {
        const uint32_t al = pack_bf16(st_lo.x, st_lo.x), ml = pack_bf16(-st_lo.y, -st_lo.y);
        const uint32_t ah = pack_bf16(st_hi.x, st_hi.x), mh = pack_bf16(-st_hi.y, -st_hi.y);
        const int m = lane >> 3;
        const uint32_t st = sb + OFF_STG + (16 + 64 * w + 16 * wq + (m & 1) * 8 + (lane & 7)) * KV_PITCH + (m >> 1) * 16;
        const uint32_t st_main = st + (jodd ? 32 : 0), st_rem = st + (jodd ? 0 : 128);
        static_for<0, 10>([&](auto I) {
          constexpr int isv = I.v / 5, rel = 2 * (I.v % 5), rest = rel == 8, t2 = rest ? 26 + 2 * isv : 8 + 8 * isv + rel;
          ln_tile(IC<t2>{}, al, ml, ah, mh);
          ln_tile(IC<t2 + 1>{}, al, ml, ah, mh);
          stsm4((rest ? st_rem : st_main + rel * 16) + isv * 160, qkv[2 * t2], qkv[2 * t2 + 1], qkv[2 * t2 + 2], qkv[2 * t2 + 3]);
        });
      }
      __syncwarp();
      if (lane == 0) mbar_arrive(bar(BAR_KV));
      if (warp == 7 && ti < 15) {
        uint4* halo = g_halo + (ti * 8 + tj) * (14 * 32) + lane;
        auto word = [&](int u) -> uint32_t {
          const int isv = u / 20, rel = u % 20;
          return u >= 40 ? 0u : (rel < 16 ? qkv[16 + 16 * isv + rel] : qkv[52 + 4 * isv + rel - 16]);
        };
#pragma unroll
        for (int p = 0; p < 14; p++) st_b128(halo + p * 32, word(3 * p), word(3 * p + 1), word(3 * p + 2), ep);
      }
      {
        const float qs = 0.22360679775f * 1.44269504089f;
        const uint32_t al = pack_bf16(st_lo.x * qs, st_lo.x * qs), ml = pack_bf16(-st_lo.y * qs, -st_lo.y * qs);
        const uint32_t ah = pack_bf16(st_hi.x * qs, st_hi.x * qs), mh = pack_bf16(-st_hi.y * qs, -st_hi.y * qs);
        static_for<0, 8>([&](auto T) { ln_tile(T, al, ml, ah, mh); });
        ln_tile(IC<24>{}, al, ml, ah, mh);
        ln_tile(IC<25>{}, al, ml, ah, mh);
#pragma unroll
        for (int t = 0; t < 10; t++) {
          const int ev = t < 8 ? t : 16 + t, od = t < 2 ? 24 + t : t - 2;
          qp[t][0] = jodd ? qkv[2 * od] : qkv[2 * ev];
          qp[t][1] = jodd ? qkv[2 * od + 1] : qkv[2 * ev + 1];
        }
      }
    }
    PROFW(4);

    float acc2[80];
    int u2 = 0;
    int sc2 = 0;
    auto wait_a2 = [&]() {
      wait_a();
    };
    auto wait_b2 = [&]() {
      mbar_wait(bar(BAR_B2_FULL + (u2 & 7)), (u2 >> 3) & 1);
    };
    auto step2 = [&](auto KIND, bool new_a, bool rel_a, bool last, auto&& hook_a, auto&& hook_b) {
      constexpr int kind = KIND.v;
      const uint32_t ad = (kind == 2 ? d64 : d128) + dlo(OFF_A, 16) + ra.slot * (A_SLOT >> 4);
      const uint32_t bd = d0 + (OFF_B >> 4) + ((u2 + 6) & 7) * (B2_SLOT >> 4);
      const uint32_t cur_a = ra.slot;
      constexpr uint32_t ahi = kind == 2 ? HI64 : HI128, ao = kind == 1 ? 4 : 0;
      STEPT(3);
      __syncwarp();
      wg_fence();
      wgmma_n160<0, ao, ahi, dlo(0, 2048), HI128>(acc2, ad, bd, sc2);
      sc2 = 1;
      wg_commit();
      u2++;
      if (new_a) ra.next<A_N>();
      wg_wait<1>();
      if (lane == 0) {
        if (u2 >= 2 && u2 - 2 < B2_STEPS - (int)B2_N) mbar_arrive(bar(BAR_B2_EMPTY + ((u2 - 2) & 7)));
        if (rel_a) mbar_arrive(bar(BAR_A_EMPTY + prev_a));
      }
      hook_a();
      wgmma_n160<0, ao + 2, ahi, dlo(6144, 2048), HI128>(acc2, ad, bd, 1);
      wg_commit();
      if (!last) {
        if (new_a) wait_a2();
        wait_b2();
      }
      hook_b();
      if (new_a) prev_a = cur_a;
    };
    auto tile2 = [&](bool first) {
      step2(IC<0>{}, false, !first, false, nop, nop);
      step2(IC<1>{}, true, false, false, nop, nop);
    };
    wait_a2();
    wait_b2();
    fence_regs(acc2);
    wg_fence();
    {
      const int e = g & 1;
      const int key0 = 128 * ti + 64 * w + 16 * wq - 16;
      uint32_t vmask = 0;
#pragma unroll
      for (int kt = 0; kt < 4; kt++) {
        const int c = 8 * kt + 2 * tq + e;
        const int dl = g + 16 - c, dh = g + 24 - c;
        if (dl >= 0 && dl <= 14 && key0 + c >= 0) vmask |= 1u << kt;
        if (dh >= 0 && dh <= 14 && key0 + c >= 0) vmask |= 16u << kt;
      }
      const uint32_t kv_ld = sb + OFF_STG + (64 * w + 16 * wq + lane) * KV_PITCH;
      uint4 hv[14];
      const uint4* hsrc = g_halo + ((ti - 1) * 8 + tj) * (14 * 32) + lane;
      static_for<0, 12>([&](auto Q) {
        constexpr int q = Q.v, hf = q & 1;
        if constexpr (q == 6) { if (f_slice(4 * kh).wide) step2(IC<2>{}, true, true, false, nop, nop); }
        step2(IC<hf>{}, hf == 1, hf == 0 && q != 0, false, nop,
              [&]() {
                if constexpr (q == FK_HALO_Q) {
                  if (warp == 0) {
#pragma unroll
                    for (int p = 0; p < 14; p++) hv[p] = ti > 0 ? ld_b128(hsrc + p * 32) : make_uint4(0, 0, 0, ep);
                  }
                }
                if constexpr (q == FK_ATT_Q) {
                  if (warp == 0) {
                    uint32_t spins = 0;
                    while (true) {
                      bool ok = true;
#pragma unroll
                      for (int p = 0; p < 14; p++) ok = ok && hv[p].w == ep;
                      ok = ok && (hv[13].y | hv[13].z) == 0;
                      if (__all_sync(0xffffffffu, ok)) break;
#pragma unroll
                      for (int p = 0; p < 14; p++) hv[p] = ld_b128(hsrc + p * 32);
                      if (++spins > (1u << 22)) __trap();
                    }
                    const uint32_t hd = sb + OFF_STG + g * KV_PITCH + tq * 4;
                    const uint32_t hm = hd + (jodd ? 32 : 0), hr = hd + (jodd ? 0 : 128);
#pragma unroll
                    for (int u = 0; u < 40; u++) {
                      const uint32_t wv = (u % 3 == 0) ? hv[u / 3].x : (u % 3 == 1) ? hv[u / 3].y : hv[u / 3].z;
                      const int rel = u % 20;
                      const uint32_t a = (rel < 16 ? hm + (rel >> 1) * 16 : hr + ((rel - 16) >> 1) * 16) + (u / 20) * 160 +
                                         (rel & 1) * 8 * KV_PITCH;
                      asm volatile("st.shared.u32 [%0], %1;" ::"r"(a), "r"(wv) : "memory");
                    }
                    __syncwarp();
                  }
                  mbar_wait(bar(BAR_KV), 0);
                  PROFW(5);
                  uint32_t op[10][2];
                  {
                    Attn a0, a1;
                    attn_scores<0>(a0, qp, kv_ld, tq);
                    attn_scores<2>(a1, qp, kv_ld, tq);
                    attn_softmax(a0, vmask, e);
                    attn_softmax(a1, vmask, e);
                    attn_values<0>(a0, op, kv_ld, tq);
                    attn_values<2>(a1, op, kv_ld, tq);
                  }
                  __syncwarp();
                  if (lane == 0) mbar_arrive(bar(BAR_ATT));
                  mbar_wait(bar(BAR_ATT), 0);
                  const int m = lane >> 3;
                  const uint32_t oa = sb + OFF_STG + (64 * w + 16 * wq + (m & 1) * 8 + (lane & 7)) * 160 + (m >> 1) * 16;
#pragma unroll
                  for (int t = 0; t < 10; t += 2) stsm4(oa + t * 16, op[t][0], op[t][1], op[t + 1][0], op[t + 1][1]);
                  fence_async_smem();
                  __syncwarp();
                  PROFW(6);
                }
                if constexpr (q >= FK_ATT_Q && q < FK_ATT_Q + 4) {
                  if (wq == q - FK_ATT_Q && lane == 0) {
                    tma2d_store(&maps.o_st, 80 * tj, 128 * ti + 64 * w + 16 * wq, sb + OFF_STG + (64 * w + 16 * wq) * 160);
                    asm volatile("cp.async.bulk.commit_group;" ::: "memory");
                  }
                }
                if constexpr (q == FK_ATT_Q + 6) {
                  if (lane == 0) { asm volatile("cp.async.bulk.wait_group 0;" ::: "memory"); mbar_arrive(bar(BAR_O_W)); }
                }
              });
      });
      if (f_slice(4 * kh + 1).wide) step2(IC<2>{}, true, true, false, nop, nop);
    }
    PROFW(9);
#pragma unroll 1
    for (int s = 2; s < 4; s++) {
#pragma unroll 1
      for (int t = 0; t < 3; t++) tile2(false);
      if (f_slice(4 * kh + s).wide) step2(IC<2>{}, true, true, false, nop, nop);
    }
    PROFW(10);
#pragma unroll 1
    for (int t = 0; t < 5; t++) {
      step2(IC<0>{}, false, true, false, nop, nop);
      step2(IC<1>{}, true, false, t == 4, nop, nop);
    }
    wg_wait<0>();
    fence_regs(acc2);
    PROFW(11);
    GT(21);

    {
      mbar_wait(bar(BAR_XR), 0);
      const int rl = 64 * w + 16 * wq + g;
      static_for<0, 10>([&](auto R) {
        constexpr int r = R.v;
        uint32_t x0, x1, bw;
        const uint32_t xa = r < 6 ? sb + OFF_XR + rl * 128 + ((r ^ (rl & 7)) << 4) + tq * 4
                                  : sb + OFF_XR + 16384 + rl * 64 + (((r - 6) ^ ((rl >> 1) & 3)) << 4) + tq * 4;
        asm volatile("ld.shared.u32 %0, [%1];" : "=r"(x0) : "r"(xa));
        asm volatile("ld.shared.u32 %0, [%1];" : "=r"(x1) : "r"(xa + (r < 6 ? 8 * 128 : 8 * 64)));
        asm volatile("ld.shared.u32 %0, [%1];" : "=r"(bw) : "r"(sb + OFF_B2 + (r * 4 + tq) * 4));
        const float a0 = bf_lo(bw) + bf_lo(x0), a1 = bf_hi(bw) + bf_hi(x0), a2 = bf_lo(bw) + bf_lo(x1), a3 = bf_hi(bw) + bf_hi(x1);
        if (kh) { acc2[40 + 4 * r] += a0; acc2[41 + 4 * r] += a1; acc2[42 + 4 * r] += a2; acc2[43 + 4 * r] += a3; }
        else { acc2[4 * r] += a0; acc2[4 * r + 1] += a1; acc2[4 * r + 2] += a2; acc2[4 * r + 3] += a3; }
      });
      PROFW(12);
      const int m = lane >> 3, row = 16 * wq + (m & 1) * 8 + (lane & 7);
      const uint32_t o128 = sb + OFF_A + w * 8192 + row * 128, x128 = ((row & 7) ^ (m >> 1)) << 4;
      const uint32_t o64 = sb + OFF_A + 32768 + w * 8192 + row * 64, x64 = (((row >> 1) & 3) ^ (m >> 1)) << 4;
#pragma unroll
      for (int t = 0; t < 20; t += 2) {
        const uint32_t addr = t < 16 ? o128 + (t >> 3) * 16384 + (x128 ^ ((t & 7) << 4)) : o64 + (x64 ^ ((t - 16) << 4));
        stsm4(addr, pack_bf16(acc2[4 * t], acc2[4 * t + 1]), pack_bf16(acc2[4 * t + 2], acc2[4 * t + 3]),
              pack_bf16(acc2[4 * t + 4], acc2[4 * t + 5]), pack_bf16(acc2[4 * t + 6], acc2[4 * t + 7]));
      }
      fence_async_smem();
      __syncwarp();
      if (lane == 0) {
        mbar_wait(bar(BAR_ZERO), 0);
        const int row0 = 128 * ti + 64 * w + 16 * wq;
        tma2d_add(&maps.out64, omain, row0, sb + OFF_A + w * 8192 + wq * 2048);
        tma2d_add(&maps.out64, omain + 64, row0, sb + OFF_A + 16384 + w * 8192 + wq * 2048);
        tma2d_add(&maps.out32, orem, row0, sb + OFF_A + 32768 + w * 8192 + wq * 1024);
        asm volatile("cp.async.bulk.commit_group;" ::: "memory");
        asm volatile("cp.async.bulk.wait_group.read 0;" ::: "memory");
      }
      PROFW(13);
    }
    cluster_sync_tail();
    GT(23);
  }
}

typedef CUresult (*EncodeFn)(CUtensorMap*, CUtensorMapDataType, cuuint32_t, void*, const cuuint64_t*, const cuuint64_t*,
                             const cuuint32_t*, const cuuint32_t*, CUtensorMapInterleave, CUtensorMapSwizzle,
                             CUtensorMapL2promotion, CUtensorMapFloatOOBfill);

static void encode(EncodeFn fn, CUtensorMap* m, const void* base, int rank, const cuuint64_t* dims,
                   const cuuint64_t* strides, const cuuint32_t* box, CUtensorMapSwizzle sw) {
  const cuuint32_t es[3] = {1, 1, 1};
  fn(m, CU_TENSOR_MAP_DATA_TYPE_BFLOAT16, rank, const_cast<void*>(base), dims, strides, box, es,
     CU_TENSOR_MAP_INTERLEAVE_NONE, sw, CU_TENSOR_MAP_L2_PROMOTION_L2_128B, CU_TENSOR_MAP_FLOAT_OOB_FILL_NONE);
}

}

extern "C" void kernel_launch(void* const* d_in, const int* in_sizes, int n_in, void* d_out, int out_size) {
  using namespace fk;
  (void)in_sizes; (void)n_in; (void)out_size;
  const bf16* x = (const bf16*)d_in[0];
  const bf16* wqkv = (const bf16*)d_in[1];
  const bf16* wo = (const bf16*)d_in[2];
  const bf16* w1 = (const bf16*)d_in[4];
  const bf16* b1 = (const bf16*)d_in[5];
  const bf16* w2 = (const bf16*)d_in[6];
  const bf16* b2 = (const bf16*)d_in[7];

  static EncodeFn enc = nullptr;
  static void* o_ptr = nullptr;
  static void* h_ptr = nullptr;
  if (!enc) {
    void* fn = nullptr;
    cudaDriverEntryPointQueryResult qr;
    cudaGetDriverEntryPoint("cuTensorMapEncodeTiled", &fn, cudaEnableDefault, &qr);
    enc = (EncodeFn)fn;
    cudaGetSymbolAddress(&o_ptr, g_o);
    cudaGetSymbolAddress(&h_ptr, g_h);
    cudaFuncSetAttribute(fused_kernel, cudaFuncAttributeMaxDynamicSharedMemorySize, SMEM_BYTES);
  }
  Maps m;
  const CUtensorMapSwizzle S128 = CU_TENSOR_MAP_SWIZZLE_128B, S64 = CU_TENSOR_MAP_SWIZZLE_64B, S32 = CU_TENSOR_MAP_SWIZZLE_32B;
  {
    const cuuint64_t d[2] = {640, 2048}, s[1] = {1280};
    const cuuint32_t b[2] = {64, 128};
    encode(enc, &m.x, x, 2, d, s, b, S128);
    encode(enc, &m.o, o_ptr, 2, d, s, b, S128);
  }
  {
    const cuuint64_t d[3] = {640, 640, 3}, s[2] = {3840, 1280};
    const cuuint32_t bm[3] = {64, 16, 3}, br[3] = {16, 16, 3};
    encode(enc, &m.wqkv_m, wqkv, 3, d, s, bm, S128);
    encode(enc, &m.wqkv_r, wqkv, 3, d, s, br, S32);
  }
  {
    const cuuint64_t d[3] = {1600, 640, 3}, s[2] = {3456, 128};
    const cuuint32_t bm[3] = {64, 16, 3};
    encode(enc, &m.w1_m, w1, 3, d, s, bm, S128);
    const cuuint64_t d2[2] = {1728, 640}, s2[1] = {3456};
    const cuuint32_t br[2] = {32, 16};
    encode(enc, &m.w1_r, w1, 2, d2, s2, br, S128);
  }
  {
    const cuuint64_t s[2] = {1280, 128}, s2[1] = {1280};
    const cuuint32_t bm[3] = {64, 16, 2}, br[2] = {32, 16};
    const cuuint64_t do3[3] = {576, 640, 2}, do2[2] = {640, 640};
    encode(enc, &m.wo_m, wo, 3, do3, s, bm, S128);
    encode(enc, &m.wo_r, wo, 2, do2, s2, br, S128);
    const cuuint64_t d23[3] = {576, 1728, 2}, d22[2] = {640, 1728};
    encode(enc, &m.w2_m, w2, 3, d23, s, bm, S128);
    encode(enc, &m.w2_r, w2, 2, d22, s2, br, S128);
  }
  {
    const cuuint64_t d[2] = {1728, 2048}, s[1] = {3456};
    const cuuint32_t bs[2] = {64, 16}, bs32[2] = {32, 16};
    encode(enc, &m.h_st, h_ptr, 2, d, s, bs, S128);
    encode(enc, &m.h_st32, h_ptr, 2, d, s, bs32, S64);
    const cuuint32_t bl[2] = {64, 128}, bl32[2] = {32, 128};
    encode(enc, &m.h_ml, h_ptr, 2, d, s, bl, S128);
    encode(enc, &m.h_rl, h_ptr, 2, d, s, bl32, S64);
  }
  {
    const cuuint64_t dq[2] = {1920, 640}, sq[1] = {3840}, d1[2] = {1728, 640}, s1[1] = {3456};
    const cuuint32_t b[2] = {16, 160};
    encode(enc, &m.cs_q, wqkv, 2, dq, sq, b, CU_TENSOR_MAP_SWIZZLE_NONE);
    encode(enc, &m.cs_1, w1, 2, d1, s1, b, CU_TENSOR_MAP_SWIZZLE_NONE);
    const cuuint64_t dx[2] = {640, 2048}, sx[1] = {1280};
    const cuuint32_t bx[2] = {128, 16};
    encode(enc, &m.xs, x, 2, dx, sx, bx, CU_TENSOR_MAP_SWIZZLE_NONE);
    const cuuint32_t bo[2] = {80, 16};
    encode(enc, &m.o_st, o_ptr, 2, dx, sx, bo, CU_TENSOR_MAP_SWIZZLE_NONE);
    const cuuint32_t b32x[2] = {32, 128};
    encode(enc, &m.x32, x, 2, dx, sx, b32x, S64);
    const cuuint32_t bo64[2] = {64, 16}, bo32[2] = {32, 16};
    encode(enc, &m.out64, d_out, 2, dx, sx, bo64, S128);
    encode(enc, &m.out32, d_out, 2, dx, sx, bo32, S64);
  }
  cudaLaunchConfig_t cfg = {};
  cfg.gridDim = dim3(kCtas);
  cfg.blockDim = dim3(kThreads);
  cfg.dynamicSmemBytes = SMEM_BYTES;
  cfg.stream = cudaStreamPerThread;
  cudaLaunchAttribute attr[1];
  attr[0].id = cudaLaunchAttributeClusterDimension;
  attr[0].val.clusterDim.x = 2;
  attr[0].val.clusterDim.y = 1;
  attr[0].val.clusterDim.z = 1;
  cfg.attrs = attr;
  cfg.numAttrs = 1;
  cudaLaunchKernelEx(&cfg, fused_kernel, m, x, wqkv, wo, w1, b1, w2, b2, (bf16*)d_out);
}
```

```cpp
#include <cuda_runtime.h>
#include <cuda_bf16.h>
#include <cuda.h>
#include <stdint.h>

#define FK_MAP 0
#define FK_GELU_PIPE 0
#define FK_LATE_WG 2
#define FK_WAITV 2
#define FK_ATT_Q 5
#define FK_HALO_Q 2

namespace fk {

typedef __nv_bfloat16 bf16;

constexpr int kS = 2048, kD = 640, kF = 1728;
constexpr int kThreads = 384;
constexpr int kCtas = 128;

constexpr uint32_t A_SLOT = 16384, A_N = 4;
constexpr uint32_t B_SLOT = 16384, B_N = 6;
constexpr uint32_t OFF_A = 0;
constexpr uint32_t OFF_B = OFF_A + A_N * A_SLOT;
constexpr uint32_t OFF_STG = OFF_B + B_N * B_SLOT;
constexpr uint32_t STG_BYTES = 3 * 16384 + 8192;
constexpr uint32_t B2_SLOT = 12288, B2_N = 8;
constexpr int B2_STEPS = 37;
constexpr uint32_t OFF_C = OFF_STG + STG_BYTES;
constexpr uint32_t OFF_CB = OFF_C + 240 * 4;
constexpr uint32_t OFF_CQ = OFF_CB + 112 * 8;
constexpr uint32_t OFF_B2 = OFF_CQ + 480;
constexpr uint32_t OFF_BAR = OFF_B2 + 160;
constexpr uint32_t OFF_ROWP = OFF_STG + 40960;
constexpr uint32_t OFF_COLP = OFF_ROWP + 4352;
constexpr uint32_t OFF_XR = OFF_STG + 24576;
constexpr uint32_t KV_PITCH = 336;

enum : uint32_t {
  BAR_A_FULL = 0, BAR_A_EMPTY = 4,
  BAR_B_FULL = 8, BAR_B_EMPTY = 14, BAR_B_PEER = 20,
  BAR_B2_FULL = 26, BAR_B2_EMPTY = 34, BAR_B2_PEER = 42,
  BAR_PROL = 50, BAR_AUX, BAR_KV, BAR_HALO_R, BAR_HALO_W, BAR_O_W, BAR_H_ST0, BAR_H_ST1, BAR_HDONE,
  BAR_CS_FULL, BAR_H_RDY, BAR_O_RDY, BAR_CS2_FULL, BAR_PROL2, BAR_AUX2, BAR_ATT, BAR_EPOCH, BAR_XR, BAR_XROWS, BAR_ZERO, BAR_ROWP, BAR_COLC, BAR_GO, BAR_HT0, BAR_HT1, BAR_HT2, BAR_HT3, BAR_DONE, BAR_COUNT
};
static_assert(BAR_COUNT <= 84, "12 warps x 7 barriers");
constexpr uint32_t OFF_EPOCH = OFF_BAR + 84 * 8;
constexpr uint32_t SMEM_BYTES = OFF_EPOCH + 16;

constexpr int FL_DONE = 0, FL_O = 1, FL_H = FL_O + 32, FL_Z = FL_H + 128, FL_COUNT = FL_Z + 64;

__device__ __align__(1024) bf16 g_o[kS * kD];
__device__ __align__(1024) bf16 g_h[kS * kF];
__device__ uint4 g_stats[kS];
__device__ uint4 g_csum[2 * 8 * 16 * 6];
__device__ uint4 g_halo[128 * 14 * 32];
__device__ unsigned g_flags[FL_COUNT * 8];

struct alignas(64) Maps {
  CUtensorMap x, wqkv_m, wqkv_r, w1_m, w1_r, wo_m, wo_r, w2_m, w2_r, o, h_ml, h_rl, cs_q, cs_1, xs, o_st, x32, out64, out32;
};

__device__ __forceinline__ uint32_t smem_u32(const void* p) { return (uint32_t)__cvta_generic_to_shared(p); }
__device__ __forceinline__ void mbar_init(uint32_t bar, uint32_t cnt) {
  asm volatile("mbarrier.init.shared::cta.b64 [%0], %1;" ::"r"(bar), "r"(cnt) : "memory");
}
__device__ __forceinline__ void mbar_expect_tx(uint32_t bar, uint32_t bytes) {
  asm volatile("mbarrier.arrive.expect_tx.shared::cta.b64 _, [%0], %1;" ::"r"(bar), "r"(bytes) : "memory");
}
__device__ __forceinline__ void mbar_arrive(uint32_t bar) {
  asm volatile("mbarrier.arrive.shared::cta.b64 _, [%0];" ::"r"(bar) : "memory");
}
#define FK_TRY "mbarrier.try_wait.parity.shared::cta.b64 p, [%0], %1;\n@p bra WAIT_DONE;\n"
__device__ __forceinline__ void mbar_wait(uint32_t bar, uint32_t parity) {
  asm volatile("{\n.reg .pred p;\n"
               "WAIT_LOOP:\n" FK_TRY
               "mbarrier.test_wait.parity.shared::cta.b64 p, [%0], %1;\n@!p bra WAIT_LOOP;\nWAIT_DONE:\n}"
               ::"r"(bar), "r"(parity) : "memory");
}
__device__ __forceinline__ void mbar_wait_long(uint32_t bar, uint32_t parity) {
  asm volatile("{\n.reg .pred p;\n.reg .u32 c;\nmov.u32 c, 0;\n"
               "WAIT_LOOP:\n" FK_TRY FK_TRY
               "add.u32 c, c, 1;\nsetp.lt.u32 p, c, 0x800000;\n@p bra WAIT_LOOP;\ntrap;\nWAIT_DONE:\n}"
               ::"r"(bar), "r"(parity) : "memory");
}
__device__ __forceinline__ bool elect_one() {
  uint32_t p;
  asm volatile("{\n.reg .pred q;\nelect.sync _|q, 0xffffffff;\nselp.u32 %0, 1, 0, q;\n}" : "=r"(p));
  return p != 0;
}
__device__ __forceinline__ void mbar_arrive_if(bool c, uint32_t bar) {
  asm volatile("{\n.reg .pred q;\nsetp.ne.u32 q, %1, 0;\n@q mbarrier.arrive.shared::cta.b64 _, [%0];\n}" ::"r"(bar), "r"((uint32_t)c) : "memory");
}
__device__ __forceinline__ unsigned ld_relaxed(const unsigned* p) {
  unsigned v;
  asm volatile("ld.relaxed.gpu.global.u32 %0, [%1];" : "=r"(v) : "l"(p) : "memory");
  return v;
}
__device__ __forceinline__ void flag_poll(int idx, unsigned target) {
  const unsigned* p = &g_flags[idx * 8];
  uint32_t spins = 0;
  while ((int)(ld_relaxed(p) - target) < 0) {
    __nanosleep(20);
    if (++spins > (1u << 22)) __trap();
  }
}
__device__ __forceinline__ void flag_release(int idx) {
  asm volatile("fence.acq_rel.gpu;\nfence.proxy.async;\nred.relaxed.gpu.global.add.u32 [%0], 1;" ::"l"(&g_flags[idx * 8]) : "memory");
}
__device__ __forceinline__ void flag_add(int idx) {
  asm volatile("red.relaxed.gpu.global.add.u32 [%0], 1;" ::"l"(&g_flags[idx * 8]) : "memory");
}
__device__ __forceinline__ void st_b128(uint4* p, uint32_t a, uint32_t b, uint32_t c, uint32_t d) {
  asm volatile("{\n.reg .b128 v;\n.reg .b64 lo, hi;\nmov.b64 lo, {%1, %2};\nmov.b64 hi, {%3, %4};\nmov.b128 v, {lo, hi};\n"
               "st.relaxed.gpu.global.b128 [%0], v;\n}" ::"l"(p), "r"(a), "r"(b), "r"(c), "r"(d) : "memory");
}
__device__ __forceinline__ uint4 ld_b128(const uint4* p) {
  uint4 r;
  asm volatile("{\n.reg .b128 v;\n.reg .b64 lo, hi;\nld.relaxed.gpu.global.b128 v, [%4];\nmov.b128 {lo, hi}, v;\n"
               "mov.b64 {%0, %1}, lo;\nmov.b64 {%2, %3}, hi;\n}"
               : "=r"(r.x), "=r"(r.y), "=r"(r.z), "=r"(r.w) : "l"(p) : "memory");
  return r;
}
__device__ __forceinline__ uint4 ll_wait(const uint4* p, uint32_t tag, uint32_t mask = 0xffffffffu) {
  uint4 v = ld_b128(p);
  uint32_t spins = 0;
  while (!__all_sync(mask, v.w == tag)) {
    __nanosleep(20);
    v = ld_b128(p);
    if (++spins > (1u << 22)) __trap();
  }
  return v;
}
__device__ __forceinline__ void fence_async_all() { asm volatile("fence.proxy.async;" ::: "memory"); }
__device__ __forceinline__ void fence_async_smem() { asm volatile("fence.proxy.async.shared::cta;" ::: "memory"); }

__device__ __forceinline__ void tma2d(uint32_t dst, const CUtensorMap* m, int c0, int c1, uint32_t bar) {
  asm volatile("cp.async.bulk.tensor.2d.shared::cluster.global.mbarrier::complete_tx::bytes [%0], [%1, {%3, %4}], [%2];"
               ::"r"(dst), "l"(m), "r"(bar), "r"(c0), "r"(c1) : "memory");
}
__device__ __forceinline__ void tma3d(uint32_t dst, const CUtensorMap* m, int c0, int c1, int c2, uint32_t bar) {
  asm volatile("cp.async.bulk.tensor.3d.shared::cluster.global.mbarrier::complete_tx::bytes [%0], [%1, {%3, %4, %5}], [%2];"
               ::"r"(dst), "l"(m), "r"(bar), "r"(c0), "r"(c1), "r"(c2) : "memory");
}
__device__ __forceinline__ void tma2d_mc(uint32_t dst, const CUtensorMap* m, int c0, int c1, uint32_t bar) {
  asm volatile("cp.async.bulk.tensor.2d.shared::cluster.global.mbarrier::complete_tx::bytes.multicast::cluster [%0], [%1, {%3, %4}], [%2], %5;"
               ::"r"(dst), "l"(m), "r"(bar), "r"(c0), "r"(c1), "h"((uint16_t)3) : "memory");
}
__device__ __forceinline__ void tma3d_mc(uint32_t dst, const CUtensorMap* m, int c0, int c1, int c2, uint32_t bar) {
  asm volatile("cp.async.bulk.tensor.3d.shared::cluster.global.mbarrier::complete_tx::bytes.multicast::cluster [%0], [%1, {%3, %4, %5}], [%2], %6;"
               ::"r"(dst), "l"(m), "r"(bar), "r"(c0), "r"(c1), "r"(c2), "h"((uint16_t)3) : "memory");
}
__device__ __forceinline__ void mbar_arrive_cluster(uint32_t bar, uint32_t rank) {
  asm volatile("{\n.reg .b32 ra;\nmapa.shared::cluster.u32 ra, %0, %1;\nmbarrier.arrive.shared::cluster.b64 _, [ra];\n}"
               ::"r"(bar), "r"(rank) : "memory");
}
__device__ __forceinline__ void cluster_wait() { asm volatile("barrier.cluster.wait.acquire;" ::: "memory"); }
__device__ __forceinline__ void cluster_sync_tail() {
  asm volatile("barrier.cluster.arrive.relaxed.aligned;\nbarrier.cluster.wait.aligned;" ::: "memory");
}
__device__ __forceinline__ void cluster_sync() {
  asm volatile("barrier.cluster.arrive.release.aligned;\nbarrier.cluster.wait.acquire.aligned;" ::: "memory");
}
struct FSlice { int a0, r0; bool wide; };
__device__ __forceinline__ FSlice f_slice(int j) {
  const int s32 = (int)((0x2F28221B140D0600ull >> (8 * j)) & 0xFF);
  FSlice f;
  f.a0 = 32 * (s32 + (s32 & 1));
  f.r0 = (s32 & 1) ? 32 * s32 : 32 * s32 + 192;
  f.wide = (j != 0) && (j != 5);
  return f;
}
__device__ __forceinline__ void tma2d_store(const CUtensorMap* m, int c0, int c1, uint32_t src) {
  asm volatile("cp.async.bulk.tensor.2d.global.shared::cta.bulk_group [%0, {%2, %3}], [%1];"
               ::"l"(m), "r"(src), "r"(c0), "r"(c1) : "memory");
}
__device__ __forceinline__ void tma3d_store(const CUtensorMap* m, int c0, int c1, int c2, uint32_t src) {
  asm volatile("cp.async.bulk.tensor.3d.global.shared::cta.bulk_group [%0, {%2, %3, %4}], [%1];"
               ::"l"(m), "r"(src), "r"(c0), "r"(c1), "r"(c2) : "memory");
}
__device__ __forceinline__ void tma2d_add(const CUtensorMap* m, int c0, int c1, uint32_t src) {
  asm volatile("cp.reduce.async.bulk.tensor.2d.global.shared::cta.add.tile.bulk_group [%0, {%2, %3}], [%1];"
               ::"l"(m), "r"(src), "r"(c0), "r"(c1) : "memory");
}
__device__ __forceinline__ void prefetch_map(const CUtensorMap* m) {
  asm volatile("prefetch.tensormap [%0];" ::"l"(m) : "memory");
}
__device__ __forceinline__ void l2_prefetch(const void* p, uint32_t bytes) {
  asm volatile("cp.async.bulk.prefetch.L2.global [%0], %1;" ::"l"(p), "r"(bytes) : "memory");
}

__host__ __device__ constexpr uint32_t dlo(uint32_t off, uint32_t lbo) { return (off >> 4) + ((lbo >> 4) << 16); }
__host__ __device__ constexpr uint32_t dhi(uint32_t sbo, uint32_t mode) { return (sbo >> 4) | (mode << 30); }
constexpr uint32_t HI128 = dhi(1024, 1), HI64 = dhi(512, 2), HI32 = dhi(256, 3);
__device__ __forceinline__ void wg_fence() { asm volatile("wgmma.fence.sync.aligned;" ::: "memory"); }
__device__ __forceinline__ void wg_commit() { asm volatile("wgmma.commit_group.sync.aligned;" ::: "memory"); }
template <int N> __device__ __forceinline__ void wg_wait() {
  asm volatile("wgmma.wait_group.sync.aligned %0;" ::"n"(N) : "memory");
}
template <int T> __device__ __forceinline__ void fence_regs(float (&d)[T]) {
#pragma unroll
  for (int i = 0; i < T; i++) asm volatile("" : "+f"(d[i])::"memory");
}

template <int O, uint32_t AOFF, uint32_t AHI, uint32_t BOFF, uint32_t BHI, int T>
__device__ __forceinline__ void wgmma_n192(float (&d)[T], uint32_t abase, uint32_t bbase, int sc) {
  asm volatile("{\n.reg .pred p;\n.reg .b32 lo;\n.reg .b64 da, db;\n"
    "add.u32 lo, %96, %98;\nmov.b64 da, {lo, %99};\n"
    "add.u32 lo, %97, %100;\nmov.b64 db, {lo, %101};\n"
    "setp.ne.b32 p, %102, 0;\n"
    "wgmma.mma_async.sync.aligned.m64n192k16.f32.bf16.bf16 "
    "{%0, %1, %2, %3, %4, %5, %6, %7, %8, %9, %10, %11, %12, %13, %14, %15, %16, %17, %18, %19, %20, %21, %22, %23, %24, %25, %26, %27, %28, %29, %30, %31, %32, %33, %34, %35, %36, %37, %38, %39, %40, %41, %42, %43, %44, %45, %46, %47, %48, %49, %50, %51, %52, %53, %54, %55, %56, %57, %58, %59, %60, %61, %62, %63, %64, %65, %66, %67, %68, %69, %70, %71, %72, %73, %74, %75, %76, %77, %78, %79, %80, %81, %82, %83, %84, %85, %86, %87, %88, %89, %90, %91, %92, %93, %94, %95}, da, db, p, 1, 1, 0, 1;\n}\n"
    : "+f"(d[O + 0]), "+f"(d[O + 1]), "+f"(d[O + 2]), "+f"(d[O + 3]), "+f"(d[O + 4]), "+f"(d[O + 5]), "+f"(d[O + 6]), "+f"(d[O + 7]), "+f"(d[O + 8]), "+f"(d[O + 9]), "+f"(d[O + 10]), "+f"(d[O + 11]), "+f"(d[O + 12]), "+f"(d[O + 13]), "+f"(d[O + 14]), "+f"(d[O + 15]), "+f"(d[O + 16]), "+f"(d[O + 17]), "+f"(d[O + 18]), "+f"(d[O + 19]), "+f"(d[O + 20]), "+f"(d[O + 21]), "+f"(d[O + 22]), "+f"(d[O + 23]), "+f"(d[O + 24]), "+f"(d[O + 25]), "+f"(d[O + 26]), "+f"(d[O + 27]), "+f"(d[O + 28]), "+f"(d[O + 29]), "+f"(d[O + 30]), "+f"(d[O + 31]), "+f"(d[O + 32]), "+f"(d[O + 33]), "+f"(d[O + 34]), "+f"(d[O + 35]), "+f"(d[O + 36]), "+f"(d[O + 37]), "+f"(d[O + 38]), "+f"(d[O + 39]), "+f"(d[O + 40]), "+f"(d[O + 41]), "+f"(d[O + 42]), "+f"(d[O + 43]), "+f"(d[O + 44]), "+f"(d[O + 45]), "+f"(d[O + 46]), "+f"(d[O + 47]), "+f"(d[O + 48]), "+f"(d[O + 49]), "+f"(d[O + 50]), "+f"(d[O + 51]), "+f"(d[O + 52]), "+f"(d[O + 53]), "+f"(d[O + 54]), "+f"(d[O + 55]), "+f"(d[O + 56]), "+f"(d[O + 57]), "+f"(d[O + 58]), "+f"(d[O + 59]), "+f"(d[O + 60]), "+f"(d[O + 61]), "+f"(d[O + 62]), "+f"(d[O + 63]), "+f"(d[O + 64]), "+f"(d[O + 65]), "+f"(d[O + 66]), "+f"(d[O + 67]), "+f"(d[O + 68]), "+f"(d[O + 69]), "+f"(d[O + 70]), "+f"(d[O + 71]), "+f"(d[O + 72]), "+f"(d[O + 73]), "+f"(d[O + 74]), "+f"(d[O + 75]), "+f"(d[O + 76]), "+f"(d[O + 77]), "+f"(d[O + 78]), "+f"(d[O + 79]), "+f"(d[O + 80]), "+f"(d[O + 81]), "+f"(d[O + 82]), "+f"(d[O + 83]), "+f"(d[O + 84]), "+f"(d[O + 85]), "+f"(d[O + 86]), "+f"(d[O + 87]), "+f"(d[O + 88]), "+f"(d[O + 89]), "+f"(d[O + 90]), "+f"(d[O + 91]), "+f"(d[O + 92]), "+f"(d[O + 93]), "+f"(d[O + 94]), "+f"(d[O + 95])
    : "r"(abase), "r"(bbase), "n"(AOFF), "n"(AHI), "n"(BOFF), "n"(BHI), "r"(sc));
}

template <int O, uint32_t AOFF, uint32_t AHI, uint32_t BOFF, uint32_t BHI, int T>
__device__ __forceinline__ void wgmma_n48(float (&d)[T], uint32_t abase, uint32_t bbase, int sc) {
  asm volatile("{\n.reg .pred p;\n.reg .b32 lo;\n.reg .b64 da, db;\n"
    "add.u32 lo, %24, %26;\nmov.b64 da, {lo, %27};\n"
    "add.u32 lo, %25, %28;\nmov.b64 db, {lo, %29};\n"
    "setp.ne.b32 p, %30, 0;\n"
    "wgmma.mma_async.sync.aligned.m64n48k16.f32.bf16.bf16 "
    "{%0, %1, %2, %3, %4, %5, %6, %7, %8, %9, %10, %11, %12, %13, %14, %15, %16, %17, %18, %19, %20, %21, %22, %23}, da, db, p, 1, 1, 0, 1;\n}\n"
    : "+f"(d[O + 0]), "+f"(d[O + 1]), "+f"(d[O + 2]), "+f"(d[O + 3]), "+f"(d[O + 4]), "+f"(d[O + 5]), "+f"(d[O + 6]), "+f"(d[O + 7]), "+f"(d[O + 8]), "+f"(d[O + 9]), "+f"(d[O + 10]), "+f"(d[O + 11]), "+f"(d[O + 12]), "+f"(d[O + 13]), "+f"(d[O + 14]), "+f"(d[O + 15]), "+f"(d[O + 16]), "+f"(d[O + 17]), "+f"(d[O + 18]), "+f"(d[O + 19]), "+f"(d[O + 20]), "+f"(d[O + 21]), "+f"(d[O + 22]), "+f"(d[O + 23])
    : "r"(abase), "r"(bbase), "n"(AOFF), "n"(AHI), "n"(BOFF), "n"(BHI), "r"(sc));
}

template <int O, uint32_t AOFF, uint32_t AHI, uint32_t BOFF, uint32_t BHI, int T>
__device__ __forceinline__ void wgmma_n224(float (&d)[T], uint32_t abase, uint32_t bbase, int sc) {
  asm volatile("{\n.reg .pred p;\n.reg .b32 lo;\n.reg .b64 da, db;\n"
    "add.u32 lo, %112, %114;\nmov.b64 da, {lo, %115};\n"
    "add.u32 lo, %113, %116;\nmov.b64 db, {lo, %117};\n"
    "setp.ne.b32 p, %118, 0;\n"
    "wgmma.mma_async.sync.aligned.m64n224k16.f32.bf16.bf16 "
    "{%0, %1, %2, %3, %4, %5, %6, %7, %8, %9, %10, %11, %12, %13, %14, %15, %16, %17, %18, %19, %20, %21, %22, %23, %24, %25, %26, %27, %28, %29, %30, %31, %32, %33, %34, %35, %36, %37, %38, %39, %40, %41, %42, %43, %44, %45, %46, %47, %48, %49, %50, %51, %52, %53, %54, %55, %56, %57, %58, %59, %60, %61, %62, %63, %64, %65, %66, %67, %68, %69, %70, %71, %72, %73, %74, %75, %76, %77, %78, %79, %80, %81, %82, %83, %84, %85, %86, %87, %88, %89, %90, %91, %92, %93, %94, %95, %96, %97, %98, %99, %100, %101, %102, %103, %104, %105, %106, %107, %108, %109, %110, %111}, da, db, p, 1, 1, 0, 1;\n}\n"
    : "+f"(d[O + 0]), "+f"(d[O + 1]), "+f"(d[O + 2]), "+f"(d[O + 3]), "+f"(d[O + 4]), "+f"(d[O + 5]), "+f"(d[O + 6]), "+f"(d[O + 7]), "+f"(d[O + 8]), "+f"(d[O + 9]), "+f"(d[O + 10]), "+f"(d[O + 11]), "+f"(d[O + 12]), "+f"(d[O + 13]), "+f"(d[O + 14]), "+f"(d[O + 15]), "+f"(d[O + 16]), "+f"(d[O + 17]), "+f"(d[O + 18]), "+f"(d[O + 19]), "+f"(d[O + 20]), "+f"(d[O + 21]), "+f"(d[O + 22]), "+f"(d[O + 23]), "+f"(d[O + 24]), "+f"(d[O + 25]), "+f"(d[O + 26]), "+f"(d[O + 27]), "+f"(d[O + 28]), "+f"(d[O + 29]), "+f"(d[O + 30]), "+f"(d[O + 31]), "+f"(d[O + 32]), "+f"(d[O + 33]), "+f"(d[O + 34]), "+f"(d[O + 35]), "+f"(d[O + 36]), "+f"(d[O + 37]), "+f"(d[O + 38]), "+f"(d[O + 39]), "+f"(d[O + 40]), "+f"(d[O + 41]), "+f"(d[O + 42]), "+f"(d[O + 43]), "+f"(d[O + 44]), "+f"(d[O + 45]), "+f"(d[O + 46]), "+f"(d[O + 47]), "+f"(d[O + 48]), "+f"(d[O + 49]), "+f"(d[O + 50]), "+f"(d[O + 51]), "+f"(d[O + 52]), "+f"(d[O + 53]), "+f"(d[O + 54]), "+f"(d[O + 55]), "+f"(d[O + 56]), "+f"(d[O + 57]), "+f"(d[O + 58]), "+f"(d[O + 59]), "+f"(d[O + 60]), "+f"(d[O + 61]), "+f"(d[O + 62]), "+f"(d[O + 63]), "+f"(d[O + 64]), "+f"(d[O + 65]), "+f"(d[O + 66]), "+f"(d[O + 67]), "+f"(d[O + 68]), "+f"(d[O + 69]), "+f"(d[O + 70]), "+f"(d[O + 71]), "+f"(d[O + 72]), "+f"(d[O + 73]), "+f"(d[O + 74]), "+f"(d[O + 75]), "+f"(d[O + 76]), "+f"(d[O + 77]), "+f"(d[O + 78]), "+f"(d[O + 79]), "+f"(d[O + 80]), "+f"(d[O + 81]), "+f"(d[O + 82]), "+f"(d[O + 83]), "+f"(d[O + 84]), "+f"(d[O + 85]), "+f"(d[O + 86]), "+f"(d[O + 87]), "+f"(d[O + 88]), "+f"(d[O + 89]), "+f"(d[O + 90]), "+f"(d[O + 91]), "+f"(d[O + 92]), "+f"(d[O + 93]), "+f"(d[O + 94]), "+f"(d[O + 95]), "+f"(d[O + 96]), "+f"(d[O + 97]), "+f"(d[O + 98]), "+f"(d[O + 99]), "+f"(d[O + 100]), "+f"(d[O + 101]), "+f"(d[O + 102]), "+f"(d[O + 103]), "+f"(d[O + 104]), "+f"(d[O + 105]), "+f"(d[O + 106]), "+f"(d[O + 107]), "+f"(d[O + 108]), "+f"(d[O + 109]), "+f"(d[O + 110]), "+f"(d[O + 111])
    : "r"(abase), "r"(bbase), "n"(AOFF), "n"(AHI), "n"(BOFF), "n"(BHI), "r"(sc));
}

template <int O, uint32_t AOFF, uint32_t AHI, uint32_t BOFF, uint32_t BHI, int T>
__device__ __forceinline__ void wgmma_n160(float (&d)[T], uint32_t abase, uint32_t bbase, int sc) {
  asm volatile("{\n.reg .pred p;\n.reg .b32 lo;\n.reg .b64 da, db;\n"
    "add.u32 lo, %80, %82;\nmov.b64 da, {lo, %83};\n"
    "add.u32 lo, %81, %84;\nmov.b64 db, {lo, %85};\n"
    "setp.ne.b32 p, %86, 0;\n"
    "wgmma.mma_async.sync.aligned.m64n160k16.f32.bf16.bf16 "
    "{%0, %1, %2, %3, %4, %5, %6, %7, %8, %9, %10, %11, %12, %13, %14, %15, %16, %17, %18, %19, %20, %21, %22, %23, %24, %25, %26, %27, %28, %29, %30, %31, %32, %33, %34, %35, %36, %37, %38, %39, %40, %41, %42, %43, %44, %45, %46, %47, %48, %49, %50, %51, %52, %53, %54, %55, %56, %57, %58, %59, %60, %61, %62, %63, %64, %65, %66, %67, %68, %69, %70, %71, %72, %73, %74, %75, %76, %77, %78, %79}, da, db, p, 1, 1, 0, 1;\n}\n"
    : "+f"(d[O + 0]), "+f"(d[O + 1]), "+f"(d[O + 2]), "+f"(d[O + 3]), "+f"(d[O + 4]), "+f"(d[O + 5]), "+f"(d[O + 6]), "+f"(d[O + 7]), "+f"(d[O + 8]), "+f"(d[O + 9]), "+f"(d[O + 10]), "+f"(d[O + 11]), "+f"(d[O + 12]), "+f"(d[O + 13]), "+f"(d[O + 14]), "+f"(d[O + 15]), "+f"(d[O + 16]), "+f"(d[O + 17]), "+f"(d[O + 18]), "+f"(d[O + 19]), "+f"(d[O + 20]), "+f"(d[O + 21]), "+f"(d[O + 22]), "+f"(d[O + 23]), "+f"(d[O + 24]), "+f"(d[O + 25]), "+f"(d[O + 26]), "+f"(d[O + 27]), "+f"(d[O + 28]), "+f"(d[O + 29]), "+f"(d[O + 30]), "+f"(d[O + 31]), "+f"(d[O + 32]), "+f"(d[O + 33]), "+f"(d[O + 34]), "+f"(d[O + 35]), "+f"(d[O + 36]), "+f"(d[O + 37]), "+f"(d[O + 38]), "+f"(d[O + 39]), "+f"(d[O + 40]), "+f"(d[O + 41]), "+f"(d[O + 42]), "+f"(d[O + 43]), "+f"(d[O + 44]), "+f"(d[O + 45]), "+f"(d[O + 46]), "+f"(d[O + 47]), "+f"(d[O + 48]), "+f"(d[O + 49]), "+f"(d[O + 50]), "+f"(d[O + 51]), "+f"(d[O + 52]), "+f"(d[O + 53]), "+f"(d[O + 54]), "+f"(d[O + 55]), "+f"(d[O + 56]), "+f"(d[O + 57]), "+f"(d[O + 58]), "+f"(d[O + 59]), "+f"(d[O + 60]), "+f"(d[O + 61]), "+f"(d[O + 62]), "+f"(d[O + 63]), "+f"(d[O + 64]), "+f"(d[O + 65]), "+f"(d[O + 66]), "+f"(d[O + 67]), "+f"(d[O + 68]), "+f"(d[O + 69]), "+f"(d[O + 70]), "+f"(d[O + 71]), "+f"(d[O + 72]), "+f"(d[O + 73]), "+f"(d[O + 74]), "+f"(d[O + 75]), "+f"(d[O + 76]), "+f"(d[O + 77]), "+f"(d[O + 78]), "+f"(d[O + 79])
    : "r"(abase), "r"(bbase), "n"(AOFF), "n"(AHI), "n"(BOFF), "n"(BHI), "r"(sc));
}

__device__ __forceinline__ uint32_t pack_bf16(float lo, float hi) {
  uint32_t r;
  asm("cvt.rn.bf16x2.f32 %0, %1, %2;" : "=r"(r) : "f"(hi), "f"(lo));
  return r;
}
__device__ __forceinline__ float bf_lo(uint32_t v) { return __uint_as_float(v << 16); }
__device__ __forceinline__ float bf_hi(uint32_t v) { return __uint_as_float(v & 0xFFFF0000u); }
__device__ __forceinline__ void stsm4(uint32_t addr, uint32_t r0, uint32_t r1, uint32_t r2, uint32_t r3) {
  asm volatile("stmatrix.sync.aligned.m8n8.x4.shared.b16 [%0], {%1, %2, %3, %4};"
               ::"r"(addr), "r"(r0), "r"(r1), "r"(r2), "r"(r3) : "memory");
}
__device__ __forceinline__ void ldsm4(uint32_t (&r)[4], uint32_t addr) {
  asm volatile("ldmatrix.sync.aligned.m8n8.x4.shared.b16 {%0, %1, %2, %3}, [%4];"
               : "=r"(r[0]), "=r"(r[1]), "=r"(r[2]), "=r"(r[3]) : "r"(addr) : "memory");
}
__device__ __forceinline__ void ldsm4t(uint32_t (&r)[4], uint32_t addr) {
  asm volatile("ldmatrix.sync.aligned.m8n8.x4.trans.shared.b16 {%0, %1, %2, %3}, [%4];"
               : "=r"(r[0]), "=r"(r[1]), "=r"(r[2]), "=r"(r[3]) : "r"(addr) : "memory");
}
__device__ __forceinline__ void mma16816(float (&c)[4], uint32_t a0, uint32_t a1, uint32_t a2, uint32_t a3,
                                         uint32_t b0, uint32_t b1) {
  asm volatile("mma.sync.aligned.m16n8k16.row.col.f32.bf16.bf16.f32 {%0,%1,%2,%3}, {%4,%5,%6,%7}, {%8,%9}, {%0,%1,%2,%3};"
               : "+f"(c[0]), "+f"(c[1]), "+f"(c[2]), "+f"(c[3])
               : "r"(a0), "r"(a1), "r"(a2), "r"(a3), "r"(b0), "r"(b1));
}
__device__ __forceinline__ void mma16816_z(float (&c)[4], uint32_t a0, uint32_t a1, uint32_t a2, uint32_t a3,
                                           uint32_t b0, uint32_t b1) {
  asm volatile("mma.sync.aligned.m16n8k16.row.col.f32.bf16.bf16.f32 {%0,%1,%2,%3}, {%4,%5,%6,%7}, {%8,%9}, {%10,%10,%10,%10};"
               : "=f"(c[0]), "=f"(c[1]), "=f"(c[2]), "=f"(c[3])
               : "r"(a0), "r"(a1), "r"(a2), "r"(a3), "r"(b0), "r"(b1), "f"(0.f));
}
__device__ __forceinline__ void mma1688(float (&c)[4], uint32_t a0, uint32_t a1, uint32_t b0) {
  asm volatile("mma.sync.aligned.m16n8k8.row.col.f32.bf16.bf16.f32 {%0,%1,%2,%3}, {%4,%5}, {%6}, {%0,%1,%2,%3};"
               : "+f"(c[0]), "+f"(c[1]), "+f"(c[2]), "+f"(c[3])
               : "r"(a0), "r"(a1), "r"(b0));
}
__device__ __forceinline__ float ex2(float x) {
  float y;
  asm("ex2.approx.ftz.f32 %0, %1;" : "=f"(y) : "f"(x));
  return y;
}
__device__ __forceinline__ float tanh_fast(float x) {
  float y;
  asm("tanh.approx.f32 %0, %1;" : "=f"(y) : "f"(x));
  return y;
}
__device__ __forceinline__ float2 lds64f(uint32_t addr) {
  float2 v;
  asm volatile("ld.shared.v2.f32 {%0, %1}, [%2];" : "=f"(v.x), "=f"(v.y) : "r"(addr));
  return v;
}

#define PROF(slot)
#define PROFW(slot)
#define GT(slot)
#define INTRA(k)
#define INTRAN()
#define STEPT(k)
#define LAT(k, e)
#define TBEG()
#define TEND(var)

struct Attn {
  float s[2][4][4];
  uint32_t p[2][4][2];
  float ilo[2], ihi[2];
};
template <int H> struct HeadTile { static constexpr int T0 = (H == 0) ? 0 : (H == 1) ? 2 : (H == 2) ? 5 : 7; };

template <int H>
__device__ __forceinline__ void attn_scores(Attn& st, const uint32_t (&qp)[10][2], uint32_t kv, int tq) {
  constexpr int T0 = HeadTile<H>::T0;
  uint32_t kb[5][4];
#pragma unroll
  for (int dt = 0; dt < 5; dt++) ldsm4(kb[dt], kv + (T0 + dt) * 16);
  const uint32_t sa0 = tq < 2 ? qp[T0 + 2][0] : 0u, sa1 = tq < 2 ? qp[T0 + 2][1] : 0u;
  const uint32_t sb0 = tq < 2 ? 0u : qp[T0 + 2][0], sb1 = tq < 2 ? 0u : qp[T0 + 2][1];
#pragma unroll
  for (int kt = 0; kt < 4; kt++) {
    mma16816_z(st.s[0][kt], qp[T0][0], qp[T0][1], qp[T0 + 1][0], qp[T0 + 1][1], kb[0][kt], kb[1][kt]);
    mma16816_z(st.s[1][kt], qp[T0 + 3][0], qp[T0 + 3][1], qp[T0 + 4][0], qp[T0 + 4][1], kb[3][kt], kb[4][kt]);
  }
#pragma unroll
  for (int kt = 0; kt < 4; kt++) {
    mma1688(st.s[0][kt], sa0, sa1, kb[2][kt]);
    mma1688(st.s[1][kt], sb0, sb1, kb[2][kt]);
  }
}

__device__ __forceinline__ void attn_softmax(Attn& st, uint32_t vmask, int e) {
  float lo[2][4], hi[2][4], mlo[2], mhi[2], slo[2], shi[2];
  const float ninf = __int_as_float(0xff800000);
#pragma unroll
  for (int h = 0; h < 2; h++) {
#pragma unroll
    for (int kt = 0; kt < 4; kt++) {
      const float vlo = e ? st.s[h][kt][1] : st.s[h][kt][0];
      const float vhi = e ? st.s[h][kt][3] : st.s[h][kt][2];
      lo[h][kt] = ((vmask >> kt) & 1) ? vlo : ninf;
      hi[h][kt] = ((vmask >> (4 + kt)) & 1) ? vhi : ninf;
    }
    mlo[h] = fmaxf(fmaxf(lo[h][0], lo[h][1]), fmaxf(lo[h][2], lo[h][3]));
    mhi[h] = fmaxf(fmaxf(hi[h][0], hi[h][1]), fmaxf(hi[h][2], hi[h][3]));
  }
#pragma unroll
  for (int o = 1; o <= 2; o <<= 1)
#pragma unroll
    for (int h = 0; h < 2; h++) {
      mlo[h] = fmaxf(mlo[h], __shfl_xor_sync(0xffffffffu, mlo[h], o));
      mhi[h] = fmaxf(mhi[h], __shfl_xor_sync(0xffffffffu, mhi[h], o));
    }
  const uint32_t sel0 = e ? 0x1044 : 0x4410, sel1 = e ? 0x3244 : 0x4432;
#pragma unroll
  for (int h = 0; h < 2; h++) {
    slo[h] = 0.f; shi[h] = 0.f;
#pragma unroll
    for (int kt = 0; kt < 4; kt++) {
      const float pl = ex2(lo[h][kt] - mlo[h]), ph = ex2(hi[h][kt] - mhi[h]);
      slo[h] += pl; shi[h] += ph;
      const uint32_t pk = pack_bf16(pl, ph);
      st.p[h][kt][0] = __byte_perm(pk, 0, sel0);
      st.p[h][kt][1] = __byte_perm(pk, 0, sel1);
    }
  }
#pragma unroll
  for (int o = 1; o <= 2; o <<= 1)
#pragma unroll
    for (int h = 0; h < 2; h++) {
      slo[h] += __shfl_xor_sync(0xffffffffu, slo[h], o);
      shi[h] += __shfl_xor_sync(0xffffffffu, shi[h], o);
    }
#pragma unroll
  for (int h = 0; h < 2; h++) { st.ilo[h] = __fdividef(1.f, slo[h]); st.ihi[h] = __fdividef(1.f, shi[h]); }
}

template <int H>
__device__ __forceinline__ void attn_values(const Attn& st, uint32_t (&op)[10][2], uint32_t kv, int tq) {
  constexpr int T0 = HeadTile<H>::T0;
  uint32_t vb[5][4];
#pragma unroll
  for (int dt = 0; dt < 5; dt++) ldsm4t(vb[dt], kv + 160 + (T0 + dt) * 16);
  float o[2][3][4];
#pragma unroll
  for (int h = 0; h < 2; h++)
#pragma unroll
    for (int dt = 0; dt < 3; dt++)
      mma16816_z(o[h][dt], st.p[h][0][0], st.p[h][0][1], st.p[h][1][0], st.p[h][1][1], vb[2 * h + dt][0], vb[2 * h + dt][1]);
#pragma unroll
  for (int h = 0; h < 2; h++)
#pragma unroll
    for (int dt = 0; dt < 3; dt++)
      mma16816(o[h][dt], st.p[h][2][0], st.p[h][2][1], st.p[h][3][0], st.p[h][3][1], vb[2 * h + dt][2], vb[2 * h + dt][3]);
#pragma unroll
  for (int t = 0; t < 5; t++) {
    const int h = t < 2 ? 0 : 1, dt = t < 2 ? t : t - 2;
    float v0 = o[h][dt][0] * st.ilo[h], v1 = o[h][dt][1] * st.ilo[h], v2 = o[h][dt][2] * st.ihi[h], v3 = o[h][dt][3] * st.ihi[h];
    if (t == 2 && tq < 2) {
      v0 = o[0][2][0] * st.ilo[0]; v1 = o[0][2][1] * st.ilo[0]; v2 = o[0][2][2] * st.ihi[0]; v3 = o[0][2][3] * st.ihi[0];
    }
    op[T0 + t][0] = pack_bf16(v0, v1);
    op[T0 + t][1] = pack_bf16(v2, v3);
  }
}

__device__ __forceinline__ uint32_t h_stage_addr(uint32_t sb, int t, int w, int wq, int lane) {
  const int m = lane >> 3;
  const int row = 16 * wq + (m & 1) * 8 + (lane & 7);
  if (t < 24) {
    const int chunk = (t & 7) + (m >> 1);
    return sb + OFF_STG + (t >> 3) * 16384 + w * 8192 + row * 128 + ((chunk ^ (row & 7)) << 4);
  }
  const int chunk = (t - 24) + (m >> 1);
  return sb + OFF_STG + 49152 + w * 4096 + row * 64 + ((chunk ^ ((row >> 1) & 3)) << 4);
}

__device__ __forceinline__ uint32_t fma2(uint32_t a, uint32_t b, uint32_t c) {
  uint32_t d;
  asm volatile("fma.rn.bf16x2 %0, %1, %2, %3;" : "=r"(d) : "r"(a), "r"(b), "r"(c));
  return d;
}
__device__ __forceinline__ uint32_t mul2(uint32_t a, uint32_t b) {
  uint32_t d;
  asm volatile("mul.rn.bf16x2 %0, %1, %2;" : "=r"(d) : "r"(a), "r"(b));
  return d;
}
__device__ __forceinline__ uint32_t tanh2(uint32_t a) {
  uint32_t d;
  asm volatile("tanh.approx.bf16x2 %0, %1;" : "=r"(d) : "r"(a));
  return d;
}
__device__ __forceinline__ uint32_t gelu2(uint32_t hp) {
  const uint32_t K0 = 0x3FCC3FCCu, K1 = 0x3E923E92u;
  const uint32_t u = mul2(hp, fma2(mul2(hp, hp), K1, K0));
  return fma2(hp, tanh2(u), hp);
}
struct GeluAddr { uint32_t row128, x128, row64, x64, cb; };
struct GeluStage { uint32_t hp[4], u[4]; };
struct GeluConst { uint32_t c0, b0, c1, b1; };
template <int T>
__device__ __forceinline__ void gelu_ld(GeluConst& k, const GeluAddr& a) {
  asm volatile("ld.shared.v2.u32 {%0, %1}, [%2 + %3];" : "=r"(k.c0), "=r"(k.b0) : "r"(a.cb), "n"(T * 32));
  asm volatile("ld.shared.v2.u32 {%0, %1}, [%2 + %3];" : "=r"(k.c1), "=r"(k.b1) : "r"(a.cb), "n"(T * 32 + 32));
}
template <int T>
__device__ __forceinline__ void gelu_arg(GeluStage& st, const GeluConst& k, const uint32_t (&hraw)[56], uint32_t chl,
                                         uint32_t rml, uint32_t chh, uint32_t rmh) {
  const uint32_t K0 = 0x3FCC3FCCu, K1 = 0x3E923E92u;
  const uint32_t c0 = k.c0, b0 = k.b0, c1 = k.c1, b1 = k.b1;
  st.hp[0] = fma2(hraw[2 * T], chl, fma2(rml, c0, b0));
  st.hp[1] = fma2(hraw[2 * T + 1], chh, fma2(rmh, c0, b0));
  st.hp[2] = fma2(hraw[2 * T + 2], chl, fma2(rml, c1, b1));
  st.hp[3] = fma2(hraw[2 * T + 3], chh, fma2(rmh, c1, b1));
#pragma unroll
  for (int i = 0; i < 4; i++) st.u[i] = mul2(st.hp[i], fma2(mul2(st.hp[i], st.hp[i]), K1, K0));
}
template <int T>
__device__ __forceinline__ void gelu_out(const GeluStage& st, const GeluAddr& a) {
  const uint32_t addr = (T < 24) ? a.row128 + (T >> 3) * 16384 + (a.x128 ^ ((T & 7) << 4)) : a.row64 + (a.x64 ^ ((T - 24) << 4));
  uint32_t r[4];
#pragma unroll
  for (int i = 0; i < 4; i++) r[i] = fma2(st.hp[i], tanh2(st.u[i]), st.hp[i]);
  stsm4(addr, r[0], r[1], r[2], r[3]);
}

template <int I> struct IC { static constexpr int v = I; };

template <int B, int E, class F> __device__ __forceinline__ void static_for(F&& f) {
  if constexpr (B < E) { f(IC<B>{}); static_for<B + 1, E>(f); }
}

struct Ring {
  uint32_t slot, phase;
  template <uint32_t N> __device__ __forceinline__ void next() {
    if (++slot == N) { slot = 0; phase ^= 1; }
  }
};

__global__ void __launch_bounds__(kThreads, 1)
fused_kernel(const __grid_constant__ Maps maps, const bf16* __restrict__ x, const bf16* __restrict__ wqkv,
             const bf16* __restrict__ wo, const bf16* __restrict__ w1, const bf16* __restrict__ b1,
             const bf16* __restrict__ w2, const bf16* __restrict__ b2, bf16* __restrict__ out) {
  extern __shared__ __align__(1024) uint8_t smem[];
  GT(22);
  const uint32_t sb = smem_u32(smem);
  const int tid = threadIdx.x, lane = tid & 31;
  const int warp = __shfl_sync(0xffffffffu, tid >> 5, 0);
  const int cta = blockIdx.x;
  const int rank = cta & 1, cl = cta >> 1;
  const int tj = cl >> 3, ti = 2 * (cl & 7) + rank;
  const int me = ti * 8 + tj;
  const int nt = tj & 3, kh = tj >> 2;
  auto bar = [&](uint32_t idx) { return sb + OFF_BAR + idx * 8; };

  {
    const FSlice f0 = f_slice(tj);
    const bf16* pa;
    if (tid < 256) {
      pa = x + (size_t)(128 * ti + (tid & 127)) * kD + 64 * (tid >> 7);
    } else {
      const int r = (tid - 256) >> 2, c = tid & 3;
      pa = w1 + (size_t)(32 * (r >> 4) + 16 * rank + (r & 15)) * kF + (c < 3 ? f0.a0 + 64 * c : f0.r0);
    }
    asm volatile("prefetch.global.L2 [%0];" ::"l"(pa) : "memory");
  }
  if (tid == 256) prefetch_map(&maps.x);
  if (tid == 288) { prefetch_map(&maps.w1_m); prefetch_map(&maps.w1_r); }
  if (lane == 0) {
    if (sb & 1023) __trap();
#pragma unroll
    for (int u = 0; u < 7; u++) {
      const int i = warp * 7 + u;
      const bool eight = (i >= BAR_A_EMPTY && i < BAR_B_FULL) || (i >= BAR_B_EMPTY && i < BAR_B_PEER) ||
                         (i >= BAR_B2_EMPTY && i < BAR_B2_PEER) || i == BAR_PROL || i == BAR_PROL2 || i == BAR_KV ||
                         i == BAR_O_W || i == BAR_ATT || i == BAR_XROWS || i == BAR_ROWP || (i >= BAR_HT0 && i <= BAR_DONE);
      mbar_init(bar(i), eight ? 8 : 1);
    }
    asm volatile("fence.mbarrier_init.release.cluster;" ::: "memory");
    fence_async_smem();
  }
  __syncthreads();
  asm volatile("barrier.cluster.arrive.relaxed.aligned;" ::: "memory");
  const FSlice fs = f_slice(tj);
  const bool jodd = tj & 1, nodd = nt & 1;
  const int qmain = 80 * tj + (jodd ? 16 : 0), qrem = 80 * tj + (jodd ? 0 : 64);
  const int omain = 160 * nt + (nodd ? 32 : 0), orem = 160 * nt + (nodd ? 0 : 128);

  if (warp >= 8) {
    asm volatile("setmaxnreg.dec.sync.aligned.u32 40;");
    if (warp == 8) {
      {
        PROF(0);
        Ring r{0, 1};
        auto put = [&](const CUtensorMap* m, int c0, int c1, uint32_t bytes) {
          mbar_wait_long(bar(BAR_A_EMPTY + r.slot), r.phase);
          if (elect_one()) {
            mbar_expect_tx(bar(BAR_A_FULL + r.slot), bytes);
            tma2d(sb + OFF_A + r.slot * A_SLOT, m, c0, c1, bar(BAR_A_FULL + r.slot));
          }
          r.next<A_N>();
        };
#pragma unroll 1
        for (int it = 0; it < 20; it++) put(&maps.x, 64 * (it < 10 ? it : it - 10), 128 * ti, 16384);
#pragma unroll 1
        for (int s = 0; s < 4; s++) {
          if (s == 0) mbar_wait_long(bar(BAR_H_ST0), 0);
          if (s == 1) mbar_wait_long(bar(BAR_H_RDY), 0);
          if (s == 0) PROF(2);
          const FSlice f2 = f_slice(4 * kh + ((nt + s) & 3));
#pragma unroll 1
          for (int t = 0; t < 3; t++) put(&maps.h_ml, f2.a0 + 64 * t, 128 * ti, 16384);
          if (f2.wide) put(&maps.h_rl, f2.r0, 128 * ti, 8192);
        }
        mbar_wait_long(bar(BAR_O_RDY), 0);
        PROF(1);
#pragma unroll 1
        for (int t = 0; t < 5; t++) put(&maps.o, 320 * kh + 64 * t, 128 * ti, 16384);
      }
    } else if (warp == 9) {
      {
        cluster_wait();
        Ring r{0, 1};
        const uint32_t half = sb + OFF_B + rank * 8192;
        const int k16 = 16 * rank;
        auto wait_free = [&]() {
          mbar_wait_long(bar(BAR_B_EMPTY + r.slot), r.phase);
          mbar_wait_long(bar(BAR_B_PEER + r.slot), r.phase);
        };
#pragma unroll 1
        for (int q = 0; q < 20; q++) {
          wait_free();
          if (elect_one()) {
            const uint32_t dst = half + r.slot * B_SLOT, fb = bar(BAR_B_FULL + r.slot);
            mbar_expect_tx(fb, fs.wide ? 14336 : 12288);
            tma3d_mc(dst, &maps.w1_m, fs.a0, 32 * q + k16, 0, fb);
            if (fs.wide) tma2d_mc(dst + 6144, &maps.w1_r, fs.r0, 32 * q + k16, fb);
            if (q == 8) {
              l2_prefetch((const char*)wo + cta * 6400, 6400);
              l2_prefetch((const char*)w2 + cta * 17280, 17280);
            }
          }
          r.next<B_N>();
        }
#pragma unroll 1
        for (int q = 0; q < 20; q++) {
          wait_free();
          if (elect_one()) {
            const uint32_t dst = half + r.slot * B_SLOT, fb = bar(BAR_B_FULL + r.slot);
            mbar_expect_tx(fb, 15360);
            tma3d_mc(dst, &maps.wqkv_m, qmain, 32 * q + k16, 0, fb);
            tma3d_mc(dst + 6144, &maps.wqkv_r, qrem, 32 * q + k16, 0, fb);
          }
          r.next<B_N>();
        }
        const uint32_t half2 = sb + OFF_B + rank * 6144;
        int u = 0;
        auto put2 = [&](const CUtensorMap* mm, const CUtensorMap* mr, int krow) {
          if (u < 7 && u != 1 && u != 5) {
            wait_free();
            r.next<B_N>();
            if (u == 0) { wait_free(); r.next<B_N>(); }
          }
          const uint32_t v = u & 7, par = ((u >> 3) & 1) ^ 1;
          mbar_wait_long(bar(BAR_B2_EMPTY + v), par);
          mbar_wait_long(bar(BAR_B2_PEER + v), par);
          if (elect_one()) {
            const uint32_t dst = half2 + ((v + 6) & 7) * B2_SLOT, fb = bar(BAR_B2_FULL + v);
            mbar_expect_tx(fb, 10240);
            tma3d_mc(dst, mm, omain, krow + k16, 0, fb);
            tma2d_mc(dst + 4096, mr, orem, krow + k16, fb);
          }
          u++;
        };
#pragma unroll 1
        for (int s = 0; s < 4; s++) {
          const FSlice f2 = f_slice(4 * kh + ((nt + s) & 3));
#pragma unroll 1
          for (int q = 0; q < 6; q++) put2(&maps.w2_m, &maps.w2_r, f2.a0 + 32 * q);
          if (f2.wide) put2(&maps.w2_m, &maps.w2_r, f2.r0);
        }
#pragma unroll 1
        for (int q = 0; q < 10; q++) put2(&maps.wo_m, &maps.wo_r, 320 * kh + 32 * q);
      }
    } else if (warp == 10) {
      unsigned ep = 0;
      if (lane == 0) {
        ep = *(volatile unsigned*)&g_flags[FL_DONE * 8] / kCtas + 1;
        *(volatile unsigned*)(smem + OFF_EPOCH) = ep;
        mbar_arrive(bar(BAR_EPOCH));
        atomicAdd(&g_flags[FL_DONE * 8], 1u);
        mbar_wait_long(bar(BAR_GO), 0);
        const bool has1 = ti < (fs.wide ? 14 : 12);
        mbar_expect_tx(bar(BAR_CS_FULL), (has1 ? 20480 : 0) + 20480);
#pragma unroll 1
        for (int q = 0; q < 5; q++) tma2d(sb + OFF_STG + 20480 + q * 4096, &maps.xs, 128 * q, 128 * ti + 16 * tj, bar(BAR_CS_FULL));
        if (has1) {
          const int col = ti < 12 ? fs.a0 + 16 * ti : fs.r0 + 16 * (ti - 12);
#pragma unroll 1
          for (int q = 0; q < 4; q++) tma2d(sb + OFF_STG + q * 5120, &maps.cs_1, col, 160 * q, bar(BAR_CS_FULL));
        }
      }
      ep = __shfl_sync(0xffffffffu, ep, 0);
      uint32_t b2v[4];
#pragma unroll
      for (int u = 0; u < 4; u++) {
        const int i2 = lane + 32 * u;
        const int c = 2 * i2;
        const int col = c < 192 ? fs.a0 + c : fs.r0 + c - 192;
        b2v[u] = (i2 < 112 && (c < 192 || fs.wide)) ? mul2(__ldg((const uint32_t*)(b1 + col)), 0x3F003F00u) : 0u;
      }
      {
#pragma unroll
        for (int u = 0; u < 2; u++) {
          const int i2 = lane + 32 * u, t = i2 >> 2;
          if (i2 < 40) {
            const int col = (t < 6 ? omain + 80 * kh + 8 * t : (kh ? orem : omain + 48) + 8 * (t - 6)) + 2 * (i2 & 3);
            *(uint32_t*)(smem + OFF_B2 + i2 * 4) = __ldg((const uint32_t*)(b2 + col));
          }
        }
      }
      auto publish_sums = [&](int which, uint32_t src) {
        const float4* p = (const float4*)(smem + src) + (lane & 3) + (lane >> 2) * 64;
        float4 s = make_float4(0.f, 0.f, 0.f, 0.f);
#pragma unroll 4
        for (int k = 0; k < 16; k++) { const float4 v = p[k * 4]; s.x += v.x; s.y += v.y; s.z += v.z; s.w += v.w; }
#pragma unroll
        for (int o = 4; o < 32; o <<= 1) {
          s.x += __shfl_xor_sync(0xffffffffu, s.x, o); s.y += __shfl_xor_sync(0xffffffffu, s.y, o);
          s.z += __shfl_xor_sync(0xffffffffu, s.z, o); s.w += __shfl_xor_sync(0xffffffffu, s.w, o);
        }
        float a[3];
#pragma unroll
        for (int i2 = 0; i2 < 3; i2++) {
          const int c = min(3 * lane + i2, 15), from = c >> 2, comp = c & 3;
          const float vx = __shfl_sync(0xffffffffu, s.x, from), vy = __shfl_sync(0xffffffffu, s.y, from);
          const float vz = __shfl_sync(0xffffffffu, s.z, from), vw = __shfl_sync(0xffffffffu, s.w, from);
          a[i2] = comp == 0 ? vx : comp == 1 ? vy : comp == 2 ? vz : vw;
        }
        if (lane < 6)
          st_b128(&g_csum[((which * 8 + tj) * 16 + ti) * 6 + lane], __float_as_uint(a[0]), __float_as_uint(a[1]),
                  __float_as_uint(a[2]), ep);
      };
      auto gather_sums = [&](int which, int npiece, float* dst) {
        const uint4* src = &g_csum[(which * 8 + tj) * 16 * 6];
        uint4 v[3];
        uint32_t spins = 0;
        while (true) {
          bool ok = true;
#pragma unroll
          for (int u = 0; u < 3; u++) {
            v[u] = ld_b128(src + min(lane + 32 * u, npiece * 6 - 1));
            ok = ok && v[u].w == ep;
          }
          if (__all_sync(0xffffffffu, ok)) break;
          __nanosleep(20);
          if (++spins > (1u << 22)) __trap();
        }
#pragma unroll
        for (int u = 0; u < 3; u++) {
          const int i2 = min(lane + 32 * u, npiece * 6 - 1);
          const int piece = i2 / 6, p = i2 - 6 * piece;
          float* d = dst + 16 * piece + 3 * p;
          d[0] = __uint_as_float(v[u].x);
          if (p < 5) { d[1] = __uint_as_float(v[u].y); d[2] = __uint_as_float(v[u].z); }
        }
        __syncwarp();
      };
      if (lane == 0) {
        mbar_wait_long(bar(BAR_XROWS), 0);
        if (ti < 15) {
          const int col = ti < 12 ? 640 * (ti >> 2) + qmain + 16 * (ti & 3) : 640 * (ti - 12) + qrem;
          mbar_expect_tx(bar(BAR_CS2_FULL), 20480);
#pragma unroll 1
          for (int q = 0; q < 4; q++) tma2d(sb + OFF_STG + 20480 + q * 5120, &maps.cs_q, col, 160 * q, bar(BAR_CS2_FULL));
        } else {
          mbar_arrive(bar(BAR_CS2_FULL));
        }
      }
      __syncwarp();
      PROF(10);
      mbar_wait_long(bar(BAR_PROL), 0);
      PROF(11);
      publish_sums(0, OFF_COLP);
      if (lane == 0) mbar_arrive(bar(BAR_COLC));
      PROF(8);
      mbar_wait_long(bar(BAR_ROWP), 0);
      PROF(9);
      {
        const float* rp = (const float*)(smem + OFF_ROWP);
        float4 acc4 = make_float4(0.f, 0.f, 0.f, 0.f);
#pragma unroll
        for (int k = 0; k < 8; k++) {
          const float4 v = *(const float4*)(rp + lane * 32 + ((k + lane) & 7) * 4);
          acc4.x += v.x; acc4.y += v.y; acc4.z += v.z; acc4.w += v.w;
        }
        const float s = (acc4.x + acc4.y) + (acc4.z + acc4.w), other = __shfl_xor_sync(0xffffffffu, s, 1);
        const float md = ((lane & 1) ? other : s) * (1.f / kD), m2 = ((lane & 1) ? s : other) * (1.f / kD);
        const float var = fmaxf(m2 - md * md, 0.f), mean = rp[1024 + (lane >> 1)] + md;
        const float rstd = rsqrtf(var + 1e-5f);
        const float var2 = var * rstd * rstd;
        const float rs = rstd * rsqrtf(var2 + 1e-5f);
        if ((lane & 1) == 0)
          st_b128(&g_stats[128 * ti + 16 * tj + (lane >> 1)], __float_as_uint(rstd), __float_as_uint(mean), __float_as_uint(rs), ep);
      }
      PROF(7);
      {
        float* tmp = (float*)(smem + OFF_C);
        gather_sums(0, 14, tmp);
        PROF(12);
#pragma unroll
        for (int u = 0; u < 4; u++) {
          const int i2 = lane + 32 * u;
          if (i2 < 112) *(uint2*)(smem + OFF_CB + i2 * 8) = make_uint2(pack_bf16(tmp[2 * i2], tmp[2 * i2 + 1]), b2v[u]);
        }
        __syncwarp();
      }
      if (lane == 0) { mbar_arrive(bar(BAR_AUX)); PROF(13); }
      mbar_wait_long(bar(BAR_PROL2), 0);
      publish_sums(1, OFF_STG + 49152);
      gather_sums(1, 15, (float*)(smem + OFF_C));
      {
        uint32_t pk[4];
#pragma unroll
        for (int u = 0; u < 4; u++) {
          const int i2 = min(lane + 32 * u, 119);
          const float2 cv = *(const float2*)(smem + OFF_C + i2 * 8);
          pk[u] = pack_bf16(cv.x, cv.y);
        }
#pragma unroll
        for (int u = 0; u < 4; u++)
          if (lane + 32 * u < 120) *(uint32_t*)(smem + OFF_CQ + (lane + 32 * u) * 4) = pk[u];
        __syncwarp();
      }
      if (lane == 0) mbar_arrive(bar(BAR_AUX2));
      if (lane == 0) {
#pragma unroll 1
        for (int T = 0; T < 4; T++) {
          mbar_wait_long(bar(BAR_HT0 + T), 0);
          if (T < 3) tma2d_store(&maps.h_ml, fs.a0 + 64 * T, 128 * ti, sb + OFF_STG + T * 16384);
          else if (fs.wide) tma2d_store(&maps.h_rl, fs.r0, 128 * ti, sb + OFF_STG + 49152);
        }
        asm volatile("cp.async.bulk.commit_group;" ::: "memory");
        asm volatile("cp.async.bulk.wait_group 0;" ::: "memory");
        mbar_arrive(bar(BAR_HDONE));
        mbar_arrive(bar(BAR_H_ST0));
        flag_add(FL_H + ti * 8 + tj);
        PROF(6);
      }
      __syncwarp();
      if (lane < 4) flag_poll(FL_H + ti * 8 + 4 * kh + lane, ep);
      __syncwarp();
      if (lane == 0) { mbar_arrive(bar(BAR_H_RDY)); PROF(3); }
      {
#pragma unroll 4
        for (int i2 = lane; i2 < 1280; i2 += 32) {
          const int r = i2 / 10, c = i2 - 10 * r;
          const int col = c < 6 ? omain + 80 * kh + 8 * c : (kh ? orem : omain + 48) + 8 * (c - 6);
          __stcg((uint4*)(out + (size_t)(128 * ti + r) * kD + col), make_uint4(0, 0, 0, 0));
        }
        __syncwarp();
        if (lane == 0)
          asm volatile("fence.acq_rel.gpu;\nfence.proxy.async;\nred.relaxed.gpu.global.add.u32 [%0], 1;"
                       ::"l"(&g_flags[(FL_Z + ti * 4 + nt) * 8]) : "memory");
      }
      if (lane == 0) {
        mbar_wait_long(bar(BAR_ATT), 0);
        mbar_expect_tx(bar(BAR_XR), 16384 + 8192);
        tma2d(sb + OFF_XR, &maps.x, omain + 80 * kh, 128 * ti, bar(BAR_XR));
        tma2d(sb + OFF_XR + 16384, &maps.x32, kh ? orem : omain + 48, 128 * ti, bar(BAR_XR));
        mbar_wait_long(bar(BAR_O_W), 0);
        flag_add(FL_O + ti * 2 + kh);
        PROF(14);
        flag_poll(FL_O + ti * 2 + kh, 4 * ep);
        mbar_arrive(bar(BAR_O_RDY));
        flag_poll(FL_Z + ti * 4 + nt, 2 * ep);
        asm volatile("fence.acq_rel.gpu;\nfence.proxy.async;" ::: "memory");
        mbar_arrive(bar(BAR_ZERO));
        PROF(4);
      }
    } else {
      if (lane < (int)(sizeof(Maps) / sizeof(CUtensorMap))) prefetch_map((const CUtensorMap*)&maps + lane);
      __syncwarp();
      cluster_wait();
      {
        Ring r{0, 0};
#pragma unroll 1
        for (int e = 0; e < 40; e++) {
          mbar_wait_long(bar(BAR_B_EMPTY + r.slot), r.phase);
          if (elect_one()) mbar_arrive_cluster(bar(BAR_B_PEER + r.slot), rank ^ 1);
          r.next<B_N>();
        }
#pragma unroll 1
        for (int e = 0; e < B2_STEPS - (int)B2_N; e++) {
          mbar_wait_long(bar(BAR_B2_EMPTY + (e & 7)), (e >> 3) & 1);
          if (elect_one()) mbar_arrive_cluster(bar(BAR_B2_PEER + (e & 7)), rank ^ 1);
        }
        mbar_wait_long(bar(BAR_DONE), 0);
      }
    }
  } else {
    asm volatile("setmaxnreg.inc.sync.aligned.u32 232;");
    const int w = warp >> 2, wq = warp & 3;
    const int g = lane >> 2, tq = lane & 3;
    PROFW(0);
    GT(20);

    const int row_lo = 128 * ti + 64 * w + 16 * wq + g;
    const bool lane0 = lane == 0;
    const uint32_t d0 = (sb & 0x3FFFF) >> 4;
    const uint32_t d128 = d0 + w * (8192 >> 4);
    const uint32_t d64 = d0 + w * (4096 >> 4);

    Ring ra{0, 0}, rb{0, 0};
    uint32_t prev_a = 0, prev_b = 0;
    auto wait_a = [&]() {
      mbar_wait(bar(BAR_A_FULL + ra.slot), ra.phase);
    };
    auto wait_b = [&]() {
      mbar_wait(bar(BAR_B_FULL + rb.slot), rb.phase);
    };
    auto a_desc = [&]() { return d128 + dlo(OFF_A, 16) + ra.slot * (A_SLOT >> 4); };
    auto b_desc = [&]() { return d0 + (OFF_B >> 4) + rb.slot * (B_SLOT >> 4); };
    auto nop = []() {};
    auto step1 = [&](auto HF, auto DEFER, auto&& k0, auto&& k1, bool first, bool last, auto&& hook_a, auto&& hook_b) {
      constexpr int hf = HF.v;
      const uint32_t ad = a_desc(), bd = b_desc();
      const uint32_t cur_a = ra.slot, cur_b = rb.slot;
      auto release_prev = [&]() {
        mbar_arrive_if(!first && lane0, bar(BAR_B_EMPTY + prev_b));
        if constexpr (hf == 0) mbar_arrive_if(!first && lane0, bar(BAR_A_EMPTY + prev_a));
      };
      STEPT(1);
      INTRA(0);
      __syncwarp();
      wg_fence();
      k0(ad, bd);
      wg_commit();
      rb.next<B_N>();
      if constexpr (hf == 1) ra.next<A_N>();
      if constexpr (!DEFER.v) {
        wg_wait<1>();
        release_prev();
      }
      INTRA(1);
      hook_a();
      k1(ad, bd);
      wg_commit();
      INTRA(2);
      if (!last) {
        if constexpr (hf == 1) wait_a();
        wait_b();
      }
      INTRA(3);
      hook_b();
      if constexpr (DEFER.v) {
        wg_wait<2>();
        release_prev();
      }
      INTRAN();
      prev_b = cur_b;
      if constexpr (hf == 1) prev_a = cur_a;
    };
    auto step1r = [&](int hf, auto DEFER, auto&& k0, auto&& k1, bool last, auto&& hook_a, auto&& hook_b) {
      const uint32_t ad = a_desc() + hf * 4, bd = b_desc();
      const uint32_t cur_a = ra.slot, cur_b = rb.slot;
      auto release_prev = [&]() {
        mbar_arrive_if(lane0, bar(BAR_B_EMPTY + prev_b));
        mbar_arrive_if(lane0 && hf == 0, bar(BAR_A_EMPTY + prev_a));
      };
      STEPT(1);
      __syncwarp();
      wg_fence();
      k0(ad, bd);
      wg_commit();
      rb.next<B_N>();
      if (hf == 1) ra.next<A_N>();
      if constexpr (!DEFER.v) {
        wg_wait<1>();
        release_prev();
      }
      hook_a();
      k1(ad, bd);
      wg_commit();
      if (!last) {
        if (hf == 1) wait_a();
        wait_b();
      }
      hook_b();
      if constexpr (DEFER.v) {
        wg_wait<2>();
        release_prev();
      }
      prev_b = cur_b;
      if (hf == 1) prev_a = cur_a;
    };
    auto drain1 = [&]() {
      wg_wait<0>();
      if (lane == 0) { mbar_arrive(bar(BAR_B_EMPTY + prev_b)); mbar_arrive(bar(BAR_A_EMPTY + prev_a)); }
    };

    unsigned ep = 0;
    uint4 sl = make_uint4(0, 0, 0, 0), sh = sl;
    uint32_t hraw[56];
    {
      float acch[112];
      int sc0 = 0;
      auto step_h = [&](auto HF, bool first, bool last, auto&& hook_a, auto&& hook_b) {
        constexpr int hf = HF.v;
        step1(HF, IC<0>{},
              [&](uint32_t ad, uint32_t bd) { wgmma_n224<0, hf * 4, HI128, dlo(0, 2048), HI128>(acch, ad, bd, sc0); sc0 = 1; },
              [&](uint32_t ad, uint32_t bd) { wgmma_n224<0, hf * 4 + 2, HI128, dlo(8192, 2048), HI128>(acch, ad, bd, 1); },
              first, last, hook_a, hook_b);
      };
      float ca[8];
      auto cols_load = [&](auto Q0, auto Q1, uint32_t off) {
        const uint32_t base = sb + OFF_STG + off + tid * 16;
        if constexpr (Q0.v == 0) {
#pragma unroll
          for (int q = 0; q < 8; q++) ca[q] = 0.f;
        }
#pragma unroll
        for (int q = Q0.v; q < Q1.v; q++) {
          uint32_t v0, v1, v2, v3;
          asm volatile("ld.shared.v4.u32 {%0, %1, %2, %3}, [%4];" : "=r"(v0), "=r"(v1), "=r"(v2), "=r"(v3) : "r"(base + q * 4096));
          ca[0] += bf_lo(v0); ca[1] += bf_hi(v0); ca[2] += bf_lo(v1); ca[3] += bf_hi(v1);
          ca[4] += bf_lo(v2); ca[5] += bf_hi(v2); ca[6] += bf_lo(v3); ca[7] += bf_hi(v3);
        }
      };
      auto cols_store = [&](uint32_t dst, uint32_t b) {
        *(float4*)(smem + dst + tid * 32) = make_float4(ca[0], ca[1], ca[2], ca[3]);
        *(float4*)(smem + dst + tid * 32 + 16) = make_float4(ca[4], ca[5], ca[6], ca[7]);
        __syncwarp();
        if (lane == 0) mbar_arrive(bar(b));
      };
      uint32_t xw[2][10];
      float piv[2], sd[2], sdd[2];
      auto rows_load = [&]() {
#pragma unroll
        for (int r = 0; r < 2; r++)
#pragma unroll
          for (int q = 0; q < 5; q++)
            asm volatile("ld.shared.v2.u32 {%0, %1}, [%2];" : "=r"(xw[r][2 * q]), "=r"(xw[r][2 * q + 1])
                         : "r"(sb + OFF_STG + 20480 + q * 4096 + (2 * warp + r) * 256 + lane * 8));
#pragma unroll
        for (int r = 0; r < 2; r++) { piv[r] = __shfl_sync(0xffffffffu, bf_lo(xw[r][0]), 0); sd[r] = 0.f; sdd[r] = 0.f; }
      };
      auto rows_part = [&](auto R, auto HALF) {
        constexpr int r = R.v;
        float s0 = 0.f, s1 = 0.f, t0 = 0.f, t1 = 0.f;
#pragma unroll
        for (int q = 5 * HALF.v; q < 5 * HALF.v + 5; q++) {
          const float d0v = bf_lo(xw[r][q]) - piv[r], d1v = bf_hi(xw[r][q]) - piv[r];
          s0 += d0v; s1 += d1v;
          t0 = fmaf(d0v, d0v, t0); t1 = fmaf(d1v, d1v, t1);
        }
        sd[r] += s0 + s1;
        sdd[r] += t0 + t1;
      };
      auto rows_store = [&]() {
        float* rp = (float*)(smem + OFF_ROWP);
#pragma unroll
        for (int r = 0; r < 2; r++) {
          rp[((2 * warp + r) * 2) * 32 + lane] = sd[r];
          rp[((2 * warp + r) * 2 + 1) * 32 + lane] = sdd[r];
          if (lane == 0) rp[1024 + 2 * warp + r] = piv[r];
        }
        __syncwarp();
        if (lane == 0) mbar_arrive(bar(BAR_ROWP));
      };
      wait_a();
      if (tid == 0) mbar_arrive(bar(BAR_GO));
      wait_b();
      fence_regs(acch);
      wg_fence();
      step_h(IC<0>{}, true, false, nop, nop);
      step_h(IC<1>{}, false, false, nop, nop);
      PROFW(2);
#pragma unroll 1
      for (int kt = 1; kt < 3; kt++) {
        step_h(IC<0>{}, false, false, nop, nop);
        step_h(IC<1>{}, false, false, nop, nop);
      }
      static_for<6, 20>([&](auto Q) {
        constexpr int q = Q.v;
        step_h(IC<(q & 1)>{}, false, q == 19, nop, [&]() {
          if constexpr (q == 7) {
            mbar_wait(bar(BAR_CS_FULL), 0);
            rows_load();
            __syncwarp();
            if (lane == 0) mbar_arrive(bar(BAR_XROWS));
          }
          if constexpr (q == 8) cols_load(IC<0>{}, IC<3>{}, 0);
          if constexpr (q == 9) { cols_load(IC<3>{}, IC<5>{}, 0); cols_store(OFF_COLP, BAR_PROL); PROFW(1); }
          if constexpr (q == 10) rows_part(IC<0>{}, IC<0>{});
          if constexpr (q == 11) rows_part(IC<0>{}, IC<1>{});
          if constexpr (q == 12) rows_part(IC<1>{}, IC<0>{});
          if constexpr (q == 13) { rows_part(IC<1>{}, IC<1>{}); rows_store(); }
          if constexpr (q == 16) { mbar_wait(bar(BAR_CS2_FULL), 0); cols_load(IC<0>{}, IC<3>{}, 20480); }
          if constexpr (q == 17) {
            cols_load(IC<3>{}, IC<5>{}, 20480);
            mbar_wait(bar(BAR_COLC), 0);
            cols_store(OFF_STG + 49152, BAR_PROL2);
          }
          if constexpr (q == 18) {
            mbar_wait(bar(BAR_EPOCH), 0);
            ep = *(volatile unsigned*)(smem + OFF_EPOCH);
            sl = ld_b128(&g_stats[row_lo]); sh = ld_b128(&g_stats[row_lo + 8]);
          }
        });
      });
      cluster_wait();
      drain1();
      fence_regs(acch);
      PROFW(7);
#pragma unroll
      for (int t = 0; t < 28; t++) {
        hraw[2 * t] = pack_bf16(acch[4 * t], acch[4 * t + 1]);
        hraw[2 * t + 1] = pack_bf16(acch[4 * t + 2], acch[4 * t + 3]);
      }
    }

    float2 st_lo, st_hi;
    uint32_t qp[10][2];
    {
      float acc[120];
      int sc0 = 0;
      auto step_qd = [&](auto HF, auto DEFER, bool first, bool last, auto&& hook_a, auto&& hook_b) {
        constexpr int hf = HF.v;
        step1(HF, DEFER,
              [&](uint32_t ad, uint32_t bd) {
                wgmma_n192<0, hf * 4, HI128, dlo(0, 2048), HI128>(acc, ad, bd, sc0);
                wgmma_n48<96, hf * 4, HI128, dlo(6144, 512), HI32>(acc, ad, bd, sc0);
                sc0 = 1;
              },
              [&](uint32_t ad, uint32_t bd) {
                wgmma_n192<0, hf * 4 + 2, HI128, dlo(8192, 2048), HI128>(acc, ad, bd, 1);
                wgmma_n48<96, hf * 4 + 2, HI128, dlo(8192 + 6144, 512), HI32>(acc, ad, bd, 1);
              },
              first, last, hook_a, hook_b);
      };
      auto step_q = [&](auto HF, bool first, bool last, auto&& hook_a, auto&& hook_b) { step_qd(HF, IC<0>{}, first, last, hook_a, hook_b); };
      uint32_t chl = 0, rml = 0, chh = 0, rmh = 0;
      GeluAddr ga;
      {
        const int m = lane >> 3, row = 16 * wq + (m & 1) * 8 + (lane & 7);
        ga.row128 = sb + OFF_STG + w * 8192 + row * 128;
        ga.x128 = ((row & 7) ^ (m >> 1)) << 4;
        ga.row64 = sb + OFF_STG + 49152 + w * 4096 + row * 64;
        ga.x64 = (((row >> 1) & 3) ^ (m >> 1)) << 4;
        ga.cb = sb + OFF_CB + (lane & 3) * 8;
      }
      wait_a();
      wait_b();
      fence_regs(acc);
      wg_fence();
      step_q(IC<0>{}, true, false, nop, nop);
      step_q(IC<1>{}, false, false, nop,
             [&]() {
               uint32_t spins = 0;
               while (!__all_sync(0xffffffffu, sl.w == ep && sh.w == ep)) {
                 sl = ld_b128(&g_stats[row_lo]); sh = ld_b128(&g_stats[row_lo + 8]);
                 if (++spins > (1u << 22)) __trap();
               }
               st_lo = make_float2(__uint_as_float(sl.x), __uint_as_float(sl.x) * __uint_as_float(sl.y));
               st_hi = make_float2(__uint_as_float(sh.x), __uint_as_float(sh.x) * __uint_as_float(sh.y));
               const float hl = 0.5f * __uint_as_float(sl.z), hh = 0.5f * __uint_as_float(sh.z);
               const float ml = -hl * __uint_as_float(sl.y), mh = -hh * __uint_as_float(sh.y);
               chl = pack_bf16(hl, hl); rml = pack_bf16(ml, ml);
               chh = pack_bf16(hh, hh); rmh = pack_bf16(mh, mh);
               mbar_wait(bar(BAR_AUX), 0);
               mbar_wait(bar(BAR_PROL2), 0);
             });
      int hf = 0;
      auto step_r = [&](auto DEFER, bool last, auto&& hook_a, auto&& hook_b) {
        step1r(hf, DEFER,
               [&](uint32_t ad, uint32_t bd) {
                 wgmma_n192<0, 0, HI128, dlo(0, 2048), HI128>(acc, ad, bd, 1);
                 wgmma_n48<96, 0, HI128, dlo(6144, 512), HI32>(acc, ad, bd, 1);
               },
               [&](uint32_t ad, uint32_t bd) {
                 wgmma_n192<0, 2, HI128, dlo(8192, 2048), HI128>(acc, ad, bd, 1);
                 wgmma_n48<96, 2, HI128, dlo(8192 + 6144, 512), HI32>(acc, ad, bd, 1);
               },
               last, hook_a, hook_b);
        hf ^= 1;
      };
      if (w == FK_LATE_WG) step_r(IC<0>{}, false, nop, nop);
      static_for<2, 16>([&](auto Q) {
        constexpr int q = Q.v, kt = q / 2;
        if constexpr ((q & 1) == 0) {
          constexpr int T = kt == 3 ? 0 : kt == 4 ? 1 : kt == 6 ? 2 : kt == 7 ? 3 : -1;
          step_r(IC<0>{}, false,
                 [&]() {
                   if constexpr (q == 10) mbar_wait(bar(BAR_AUX2), 0);
                 },
                 [&]() {
                   if constexpr (T >= 0) {
                     fence_async_smem();
                     __syncwarp();
                     if (lane == 0) mbar_arrive(bar(BAR_HT0 + T));
                     if constexpr (T == 3) PROFW(8);
                   }
                 });
        } else {
          constexpr int n = kt > 6 ? 0 : (kt == 2 || kt == 3) ? 3 : 2;
          constexpr int p0 = kt == 1 ? 0 : kt == 2 ? 2 : kt == 3 ? 5 : kt == 4 ? 8 : kt == 5 ? 10 : 12;
          GeluConst kc[3];
          GeluStage gs[3];
          step_r(IC<(n > 0)>{}, false,
                 [&]() { static_for<0, n>([&](auto I) { gelu_ld<2 * (p0 + I.v)>(kc[I.v], ga); }); },
                 [&]() {
                   static_for<0, n>([&](auto I) { gelu_arg<2 * (p0 + I.v)>(gs[I.v], kc[I.v], hraw, chl, rml, chh, rmh); });
                   static_for<0, n>([&](auto I) { gelu_out<2 * (p0 + I.v)>(gs[I.v], ga); });
                 });
        }
      });
#pragma unroll 1
      for (int q = (w == FK_LATE_WG) ? 17 : 16; q < 20; q++) step_r(IC<0>{}, q == 19, nop, nop);
      drain1();
      fence_regs(acc);
      PROFW(3);
      uint32_t qkv[60];
#pragma unroll
      for (int t = 0; t < 30; t++) {
        qkv[2 * t] = pack_bf16(acc[4 * t], acc[4 * t + 1]);
        qkv[2 * t + 1] = pack_bf16(acc[4 * t + 2], acc[4 * t + 3]);
      }
      mbar_wait(bar(BAR_HDONE), 0);
      mbar_wait(bar(BAR_AUX2), 0);
      auto ln_tile = [&](auto T, uint32_t al, uint32_t ml, uint32_t ah, uint32_t mh) {
        constexpr int t = T.v;
        uint32_t c2;
        asm volatile("ld.shared.u32 %0, [%1];" : "=r"(c2) : "r"(sb + OFF_CQ + (t * 4 + tq) * 4));
        qkv[2 * t] = fma2(qkv[2 * t], al, mul2(ml, c2));
        qkv[2 * t + 1] = fma2(qkv[2 * t + 1], ah, mul2(mh, c2));
      };
      {
        const uint32_t al = pack_bf16(st_lo.x, st_lo.x), ml = pack_bf16(-st_lo.y, -st_lo.y);
        const uint32_t ah = pack_bf16(st_hi.x, st_hi.x), mh = pack_bf16(-st_hi.y, -st_hi.y);
        const int m = lane >> 3;
        const uint32_t st = sb + OFF_STG + (16 + 64 * w + 16 * wq + (m & 1) * 8 + (lane & 7)) * KV_PITCH + (m >> 1) * 16;
        const uint32_t st_main = st + (jodd ? 32 : 0), st_rem = st + (jodd ? 0 : 128);
        static_for<0, 10>([&](auto I) {
          constexpr int isv = I.v / 5, rel = 2 * (I.v % 5), rest = rel == 8, t2 = rest ? 26 + 2 * isv : 8 + 8 * isv + rel;
          ln_tile(IC<t2>{}, al, ml, ah, mh);
          ln_tile(IC<t2 + 1>{}, al, ml, ah, mh);
          stsm4((rest ? st_rem : st_main + rel * 16) + isv * 160, qkv[2 * t2], qkv[2 * t2 + 1], qkv[2 * t2 + 2], qkv[2 * t2 + 3]);
        });
      }
      __syncwarp();
      if (lane == 0) mbar_arrive(bar(BAR_KV));
      if (warp == 7 && ti < 15) {
        uint4* halo = g_halo + (ti * 8 + tj) * (14 * 32) + lane;
        auto word = [&](int u) -> uint32_t {
          const int isv = u / 20, rel = u % 20;
          return u >= 40 ? 0u : (rel < 16 ? qkv[16 + 16 * isv + rel] : qkv[52 + 4 * isv + rel - 16]);
        };
#pragma unroll
        for (int p = 0; p < 14; p++) st_b128(halo + p * 32, word(3 * p), word(3 * p + 1), word(3 * p + 2), ep);
      }
      {
        const float qs = 0.22360679775f * 1.44269504089f;
        const uint32_t al = pack_bf16(st_lo.x * qs, st_lo.x * qs), ml = pack_bf16(-st_lo.y * qs, -st_lo.y * qs);
        const uint32_t ah = pack_bf16(st_hi.x * qs, st_hi.x * qs), mh = pack_bf16(-st_hi.y * qs, -st_hi.y * qs);
        static_for<0, 8>([&](auto T) { ln_tile(T, al, ml, ah, mh); });
        ln_tile(IC<24>{}, al, ml, ah, mh);
        ln_tile(IC<25>{}, al, ml, ah, mh);
#pragma unroll
        for (int t = 0; t < 10; t++) {
          const int ev = t < 8 ? t : 16 + t, od = t < 2 ? 24 + t : t - 2;
          qp[t][0] = jodd ? qkv[2 * od] : qkv[2 * ev];
          qp[t][1] = jodd ? qkv[2 * od + 1] : qkv[2 * ev + 1];
        }
      }
    }
    PROFW(4);

    float acc2[80];
    int u2 = 0;
    int sc2 = 0;
    auto wait_a2 = [&]() {
      wait_a();
    };
    auto wait_b2 = [&]() {
      mbar_wait(bar(BAR_B2_FULL + (u2 & 7)), (u2 >> 3) & 1);
    };
    auto step2 = [&](auto KIND, bool new_a, bool rel_a, bool last, auto&& hook_a, auto&& hook_b) {
      constexpr int kind = KIND.v;
      const uint32_t ad = (kind == 2 ? d64 : d128) + dlo(OFF_A, 16) + ra.slot * (A_SLOT >> 4);
      const uint32_t bd = d0 + (OFF_B >> 4) + ((u2 + 6) & 7) * (B2_SLOT >> 4);
      const uint32_t cur_a = ra.slot;
      constexpr uint32_t ahi = kind == 2 ? HI64 : HI128, ao = kind == 1 ? 4 : 0;
      STEPT(3);
      __syncwarp();
      wg_fence();
      wgmma_n160<0, ao, ahi, dlo(0, 2048), HI128>(acc2, ad, bd, sc2);
      sc2 = 1;
      wg_commit();
      u2++;
      if (new_a) ra.next<A_N>();
      wg_wait<1>();
      mbar_arrive_if(lane0 && u2 >= 2 && u2 - 2 < B2_STEPS - (int)B2_N, bar(BAR_B2_EMPTY + ((u2 - 2) & 7)));
      mbar_arrive_if(lane0 && rel_a, bar(BAR_A_EMPTY + prev_a));
      hook_a();
      wgmma_n160<0, ao + 2, ahi, dlo(6144, 2048), HI128>(acc2, ad, bd, 1);
      wg_commit();
      if (!last) {
        if (new_a) wait_a2();
        wait_b2();
      }
      hook_b();
      if (new_a) prev_a = cur_a;
    };
    auto tile2 = [&](bool first) {
      step2(IC<0>{}, false, !first, false, nop, nop);
      step2(IC<1>{}, true, false, false, nop, nop);
    };
    wait_a2();
    wait_b2();
    fence_regs(acc2);
    wg_fence();
    {
      const int e = g & 1;
      const int key0 = 128 * ti + 64 * w + 16 * wq - 16;
      uint32_t vmask = 0;
#pragma unroll
      for (int kt = 0; kt < 4; kt++) {
        const int c = 8 * kt + 2 * tq + e;
        const int dl = g + 16 - c, dh = g + 24 - c;
        if (dl >= 0 && dl <= 14 && key0 + c >= 0) vmask |= 1u << kt;
        if (dh >= 0 && dh <= 14 && key0 + c >= 0) vmask |= 16u << kt;
      }
      const uint32_t kv_ld = sb + OFF_STG + (64 * w + 16 * wq + lane) * KV_PITCH;
      uint4 hv[14];
      uint32_t op[10][2];
      const uint4* hsrc = g_halo + ((ti - 1) * 8 + tj) * (14 * 32) + lane;
      static_for<0, 12>([&](auto Q) {
        constexpr int q = Q.v, hf = q & 1;
        if constexpr (q == 6) { if (fs.wide) step2(IC<2>{}, true, true, false, nop, nop); }
        step2(IC<hf>{}, hf == 1, hf == 0 && q != 0, false, nop,
              [&]() {
                if constexpr (q == FK_HALO_Q) {
                  if (warp == 0) {
#pragma unroll
                    for (int p = 0; p < 14; p++) hv[p] = ti > 0 ? ld_b128(hsrc + p * 32) : make_uint4(0, 0, 0, ep);
                  }
                }
                if constexpr (q == FK_ATT_Q - 1) {
                  if (warp == 0) {
                    uint32_t spins = 0;
                    while (true) {
                      bool ok = true;
#pragma unroll
                      for (int p = 0; p < 14; p++) ok = ok && hv[p].w == ep;
                      ok = ok && (hv[13].y | hv[13].z) == 0;
                      if (__all_sync(0xffffffffu, ok)) break;
#pragma unroll
                      for (int p = 0; p < 14; p++) hv[p] = ld_b128(hsrc + p * 32);
                      if (++spins > (1u << 22)) __trap();
                    }
                    const uint32_t hd = sb + OFF_STG + g * KV_PITCH + tq * 4;
                    const uint32_t hm = hd + (jodd ? 32 : 0), hr = hd + (jodd ? 0 : 128);
                    static_for<0, 40>([&](auto U) {
                      constexpr int u = U.v, rel = u % 20;
                      constexpr int off = (rel < 16 ? (rel >> 1) * 16 : ((rel - 16) >> 1) * 16) + (u / 20) * 160 + (rel & 1) * 8 * KV_PITCH;
                      const uint32_t wv = (u % 3 == 0) ? hv[u / 3].x : (u % 3 == 1) ? hv[u / 3].y : hv[u / 3].z;
                      asm volatile("st.shared.u32 [%0 + %1], %2;" ::"r"(rel < 16 ? hm : hr), "n"(off), "r"(wv) : "memory");
                    });
                    __syncwarp();
                  }
                }
                if constexpr (q == FK_ATT_Q) {
                  mbar_wait(bar(BAR_KV), 0);
                  PROFW(5);
                  {
                    Attn a0, a1;
                    attn_scores<0>(a0, qp, kv_ld, tq);
                    attn_scores<2>(a1, qp, kv_ld, tq);
                    attn_softmax(a0, vmask, e);
                    attn_values<0>(a0, op, kv_ld, tq);
                    attn_softmax(a1, vmask, e);
                    attn_values<2>(a1, op, kv_ld, tq);
                  }
                  __syncwarp();
                  if (lane == 0) mbar_arrive(bar(BAR_ATT));
                }
                if constexpr (q == FK_ATT_Q + 1) {
                  mbar_wait(bar(BAR_ATT), 0);
                  const int m = lane >> 3;
                  const uint32_t oa = sb + OFF_STG + (64 * w + 16 * wq + (m & 1) * 8 + (lane & 7)) * 160 + (m >> 1) * 16;
#pragma unroll
                  for (int t = 0; t < 10; t += 2) stsm4(oa + t * 16, op[t][0], op[t][1], op[t + 1][0], op[t + 1][1]);
                  fence_async_smem();
                  __syncwarp();
                  PROFW(6);
                }
                if constexpr (q >= FK_ATT_Q + 1 && q < FK_ATT_Q + 5) {
                  if (wq == q - (FK_ATT_Q + 1) && lane == 0) {
                    tma2d_store(&maps.o_st, 80 * tj, 128 * ti + 64 * w + 16 * wq, sb + OFF_STG + (64 * w + 16 * wq) * 160);
                    asm volatile("cp.async.bulk.commit_group;" ::: "memory");
                  }
                }
                if constexpr (q == FK_ATT_Q + 6) {
                  if (lane == 0) { asm volatile("cp.async.bulk.wait_group 0;" ::: "memory"); mbar_arrive(bar(BAR_O_W)); }
                }
              });
      });
      if (f_slice(4 * kh + ((nt + 1) & 3)).wide) step2(IC<2>{}, true, true, false, nop, nop);
    }
    PROFW(9);
#pragma unroll 1
    for (int s = 2; s < 4; s++) {
#pragma unroll 1
      for (int t = 0; t < 3; t++) tile2(false);
      if (f_slice(4 * kh + ((nt + s) & 3)).wide) step2(IC<2>{}, true, true, false, nop, nop);
    }
    PROFW(10);
    float xb[40];
    step2(IC<0>{}, false, true, false, nop, nop);
    step2(IC<1>{}, true, false, false, nop, [&]() {
      mbar_wait(bar(BAR_XR), 0);
      const int rl = 64 * w + 16 * wq + g;
      static_for<0, 10>([&](auto R) {
        constexpr int r = R.v;
        uint32_t x0, x1, bw;
        const uint32_t xa = r < 6 ? sb + OFF_XR + rl * 128 + ((r ^ (rl & 7)) << 4) + tq * 4
                                  : sb + OFF_XR + 16384 + rl * 64 + (((r - 6) ^ ((rl >> 1) & 3)) << 4) + tq * 4;
        asm volatile("ld.shared.u32 %0, [%1];" : "=r"(x0) : "r"(xa));
        asm volatile("ld.shared.u32 %0, [%1];" : "=r"(x1) : "r"(xa + (r < 6 ? 8 * 128 : 8 * 64)));
        asm volatile("ld.shared.u32 %0, [%1];" : "=r"(bw) : "r"(sb + OFF_B2 + (r * 4 + tq) * 4));
        xb[4 * r] = bf_lo(bw) + bf_lo(x0); xb[4 * r + 1] = bf_hi(bw) + bf_hi(x0);
        xb[4 * r + 2] = bf_lo(bw) + bf_lo(x1); xb[4 * r + 3] = bf_hi(bw) + bf_hi(x1);
      });
    });
    wg_wait<0>();
    if (lane == 0) { mbar_arrive(bar(BAR_B2_EMPTY + ((u2 - 1) & 7))); mbar_arrive(bar(BAR_A_EMPTY + prev_a)); }
    if (w == 1) asm volatile("bar.sync 5, 256;" ::: "memory");
    __syncwarp();
    wg_fence();
#pragma unroll 1
    for (int t = 1; t < 5; t++) {
      const uint32_t ad = d128 + dlo(OFF_A, 16) + ra.slot * (A_SLOT >> 4);
      if (t > 1) wait_a2();
#pragma unroll
      for (int hf = 0; hf < 2; hf++) {
        if (t > 1 || hf > 0) wait_b2();
        const uint32_t bd = d0 + (OFF_B >> 4) + ((u2 + 6) & 7) * (B2_SLOT >> 4);
        if (hf == 0) {
          wgmma_n160<0, 0, HI128, dlo(0, 2048), HI128>(acc2, ad, bd, 1);
          wgmma_n160<0, 2, HI128, dlo(6144, 2048), HI128>(acc2, ad, bd, 1);
        } else {
          wgmma_n160<0, 4, HI128, dlo(0, 2048), HI128>(acc2, ad, bd, 1);
          wgmma_n160<0, 6, HI128, dlo(6144, 2048), HI128>(acc2, ad, bd, 1);
        }
        u2++;
      }
      ra.next<A_N>();
    }
    wg_commit();
    if (w == 0) asm volatile("bar.arrive 5, 256;" ::: "memory");
    wg_wait<0>();
    fence_regs(acc2);
    PROFW(11);
    GT(21);

    {
#pragma unroll
      for (int r = 0; r < 40; r++) {
        if (kh) acc2[40 + r] += xb[r];
        else acc2[r] += xb[r];
      }
      PROFW(12);
      const int m = lane >> 3, row = 16 * wq + (m & 1) * 8 + (lane & 7);
      const uint32_t o128 = sb + OFF_A + w * 8192 + row * 128, x128 = ((row & 7) ^ (m >> 1)) << 4;
      const uint32_t o64 = sb + OFF_A + 32768 + w * 8192 + row * 64, x64 = (((row >> 1) & 3) ^ (m >> 1)) << 4;
#pragma unroll
      for (int t = 0; t < 20; t += 2) {
        const uint32_t addr = t < 16 ? o128 + (t >> 3) * 16384 + (x128 ^ ((t & 7) << 4)) : o64 + (x64 ^ ((t - 16) << 4));
        stsm4(addr, pack_bf16(acc2[4 * t], acc2[4 * t + 1]), pack_bf16(acc2[4 * t + 2], acc2[4 * t + 3]),
              pack_bf16(acc2[4 * t + 4], acc2[4 * t + 5]), pack_bf16(acc2[4 * t + 6], acc2[4 * t + 7]));
      }
      fence_async_smem();
      __syncwarp();
      if (lane == 0) {
        mbar_wait(bar(BAR_ZERO), 0);
        const int row0 = 128 * ti + 64 * w + 16 * wq;
        tma2d_add(&maps.out64, omain, row0, sb + OFF_A + w * 8192 + wq * 2048);
        tma2d_add(&maps.out64, omain + 64, row0, sb + OFF_A + 16384 + w * 8192 + wq * 2048);
        tma2d_add(&maps.out32, orem, row0, sb + OFF_A + 32768 + w * 8192 + wq * 1024);
        asm volatile("cp.async.bulk.commit_group;" ::: "memory");
        asm volatile("cp.async.bulk.wait_group.read 0;" ::: "memory");
      }
      PROFW(13);
    }
    __syncwarp();
    if (lane == 0) mbar_arrive(bar(BAR_DONE));
    cluster_sync_tail();
    GT(23);
  }
}

typedef CUresult (*EncodeFn)(CUtensorMap*, CUtensorMapDataType, cuuint32_t, void*, const cuuint64_t*, const cuuint64_t*,
                             const cuuint32_t*, const cuuint32_t*, CUtensorMapInterleave, CUtensorMapSwizzle,
                             CUtensorMapL2promotion, CUtensorMapFloatOOBfill);

static void encode(EncodeFn fn, CUtensorMap* m, const void* base, int rank, const cuuint64_t* dims,
                   const cuuint64_t* strides, const cuuint32_t* box, CUtensorMapSwizzle sw) {
  const cuuint32_t es[3] = {1, 1, 1};
  fn(m, CU_TENSOR_MAP_DATA_TYPE_BFLOAT16, rank, const_cast<void*>(base), dims, strides, box, es,
     CU_TENSOR_MAP_INTERLEAVE_NONE, sw, CU_TENSOR_MAP_L2_PROMOTION_L2_128B, CU_TENSOR_MAP_FLOAT_OOB_FILL_NONE);
}

}

extern "C" void kernel_launch(void* const* d_in, const int* in_sizes, int n_in, void* d_out, int out_size) {
  using namespace fk;
  (void)in_sizes; (void)n_in; (void)out_size;
  const bf16* x = (const bf16*)d_in[0];
  const bf16* wqkv = (const bf16*)d_in[1];
  const bf16* wo = (const bf16*)d_in[2];
  const bf16* w1 = (const bf16*)d_in[4];
  const bf16* b1 = (const bf16*)d_in[5];
  const bf16* w2 = (const bf16*)d_in[6];
  const bf16* b2 = (const bf16*)d_in[7];

  static EncodeFn enc = nullptr;
  static void* o_ptr = nullptr;
  static void* h_ptr = nullptr;
  if (!enc) {
    void* fn = nullptr;
    cudaDriverEntryPointQueryResult qr;
    cudaGetDriverEntryPoint("cuTensorMapEncodeTiled", &fn, cudaEnableDefault, &qr);
    enc = (EncodeFn)fn;
    cudaGetSymbolAddress(&o_ptr, g_o);
    cudaGetSymbolAddress(&h_ptr, g_h);
    cudaFuncSetAttribute(fused_kernel, cudaFuncAttributeMaxDynamicSharedMemorySize, SMEM_BYTES);
  }
  Maps m;
  const CUtensorMapSwizzle S128 = CU_TENSOR_MAP_SWIZZLE_128B, S64 = CU_TENSOR_MAP_SWIZZLE_64B, S32 = CU_TENSOR_MAP_SWIZZLE_32B;
  {
    const cuuint64_t d[2] = {640, 2048}, s[1] = {1280};
    const cuuint32_t b[2] = {64, 128};
    encode(enc, &m.x, x, 2, d, s, b, S128);
    encode(enc, &m.o, o_ptr, 2, d, s, b, S128);
  }
  {
    const cuuint64_t d[3] = {640, 640, 3}, s[2] = {3840, 1280};
    const cuuint32_t bm[3] = {64, 16, 3}, br[3] = {16, 16, 3};
    encode(enc, &m.wqkv_m, wqkv, 3, d, s, bm, S128);
    encode(enc, &m.wqkv_r, wqkv, 3, d, s, br, S32);
  }
  {
    const cuuint64_t d[3] = {1600, 640, 3}, s[2] = {3456, 128};
    const cuuint32_t bm[3] = {64, 16, 3};
    encode(enc, &m.w1_m, w1, 3, d, s, bm, S128);
    const cuuint64_t d2[2] = {1728, 640}, s2[1] = {3456};
    const cuuint32_t br[2] = {32, 16};
    encode(enc, &m.w1_r, w1, 2, d2, s2, br, S128);
  }
  {
    const cuuint64_t s[2] = {1280, 128}, s2[1] = {1280};
    const cuuint32_t bm[3] = {64, 16, 2}, br[2] = {32, 16};
    const cuuint64_t do3[3] = {576, 640, 2}, do2[2] = {640, 640};
    encode(enc, &m.wo_m, wo, 3, do3, s, bm, S128);
    encode(enc, &m.wo_r, wo, 2, do2, s2, br, S128);
    const cuuint64_t d23[3] = {576, 1728, 2}, d22[2] = {640, 1728};
    encode(enc, &m.w2_m, w2, 3, d23, s, bm, S128);
    encode(enc, &m.w2_r, w2, 2, d22, s2, br, S128);
  }
  {
    const cuuint64_t d[2] = {1728, 2048}, s[1] = {3456};
    const cuuint32_t bl[2] = {64, 128}, bl32[2] = {32, 128};
    encode(enc, &m.h_ml, h_ptr, 2, d, s, bl, S128);
    encode(enc, &m.h_rl, h_ptr, 2, d, s, bl32, S64);
  }
  {
    const cuuint64_t dq[2] = {1920, 640}, sq[1] = {3840}, d1[2] = {1728, 640}, s1[1] = {3456};
    const cuuint32_t b[2] = {16, 160};
    encode(enc, &m.cs_q, wqkv, 2, dq, sq, b, CU_TENSOR_MAP_SWIZZLE_NONE);
    encode(enc, &m.cs_1, w1, 2, d1, s1, b, CU_TENSOR_MAP_SWIZZLE_NONE);
    const cuuint64_t dx[2] = {640, 2048}, sx[1] = {1280};
    const cuuint32_t bx[2] = {128, 16};
    encode(enc, &m.xs, x, 2, dx, sx, bx, CU_TENSOR_MAP_SWIZZLE_NONE);
    const cuuint32_t bo[2] = {80, 16};
    encode(enc, &m.o_st, o_ptr, 2, dx, sx, bo, CU_TENSOR_MAP_SWIZZLE_NONE);
    const cuuint32_t b32x[2] = {32, 128};
    encode(enc, &m.x32, x, 2, dx, sx, b32x, S64);
    const cuuint32_t bo64[2] = {64, 16}, bo32[2] = {32, 16};
    encode(enc, &m.out64, d_out, 2, dx, sx, bo64, S128);
    encode(enc, &m.out32, d_out, 2, dx, sx, bo32, S64);
  }
  cudaLaunchConfig_t cfg = {};
  cfg.gridDim = dim3(kCtas);
  cfg.blockDim = dim3(kThreads);
  cfg.dynamicSmemBytes = SMEM_BYTES;
  cfg.stream = cudaStreamPerThread;
  cudaLaunchAttribute attr[1];
  attr[0].id = cudaLaunchAttributeClusterDimension;
  attr[0].val.clusterDim.x = 2;
  attr[0].val.clusterDim.y = 1;
  attr[0].val.clusterDim.z = 1;
  cfg.attrs = attr;
  cfg.numAttrs = 1;
  cudaLaunchKernelEx(&cfg, fused_kernel, m, x, wqkv, wo, w1, b1, w2, b2, (bf16*)d_out);
}
```

```cpp
#include <cuda_runtime.h>
#include <cuda_bf16.h>
#include <cuda.h>
#include <stdint.h>

#define FK_MAP 0
#define FK_GELU_PIPE 0
#define FK_LATE_WG 2
#define FK_WAITV 2
#define FK_TAIL_RED 1
#define FK_ATT_Q 5
#define FK_HALO_Q 2

namespace fk {

typedef __nv_bfloat16 bf16;

constexpr int kS = 2048, kD = 640, kF = 1728;
constexpr int kThreads = 384;
constexpr int kCtas = 128;

constexpr uint32_t A_SLOT = 16384, A_N = 4;
constexpr uint32_t B_SLOT = 16384, B_N = 6;
constexpr uint32_t OFF_A = 0;
constexpr uint32_t OFF_B = OFF_A + A_N * A_SLOT;
constexpr uint32_t OFF_STG = OFF_B + B_N * B_SLOT;
constexpr uint32_t STG_BYTES = 3 * 16384 + 8192;
constexpr uint32_t B2_SLOT = 12288, B2_N = 8;
constexpr int B2_STEPS = 37;
constexpr uint32_t OFF_C = OFF_STG + STG_BYTES;
constexpr uint32_t OFF_C1 = OFF_C + 240 * 4;
constexpr uint32_t OFF_B1 = OFF_C1 + 224 * 4;
constexpr uint32_t OFF_B2 = OFF_B1 + 112 * 4;
constexpr uint32_t OFF_BAR = OFF_B2 + 160;
constexpr uint32_t OFF_ROWP = OFF_STG + 40960;
constexpr uint32_t OFF_COLP = OFF_ROWP + 4352;
constexpr uint32_t OFF_XR = OFF_STG + 24576;
constexpr uint32_t KV_PITCH = 336;

enum : uint32_t {
  BAR_A_FULL = 0, BAR_A_EMPTY = 4,
  BAR_B_FULL = 8, BAR_B_EMPTY = 14, BAR_B_PEER = 20,
  BAR_B2_FULL = 26, BAR_B2_EMPTY = 34, BAR_B2_PEER = 42,
  BAR_PROL = 50, BAR_AUX, BAR_KV, BAR_HALO_R, BAR_HALO_W, BAR_O_W, BAR_H_ST0, BAR_H_ST1, BAR_HDONE,
  BAR_CS_FULL, BAR_H_RDY, BAR_O_RDY, BAR_CS2_FULL, BAR_PROL2, BAR_AUX2, BAR_ATT, BAR_EPOCH, BAR_XR, BAR_XROWS, BAR_ZERO, BAR_ROWP, BAR_COLC, BAR_GO, BAR_HT0, BAR_HT1, BAR_HT2, BAR_HT3, BAR_DONE, BAR_COUNT
};
static_assert(BAR_COUNT <= 84, "12 warps x 7 barriers");
constexpr uint32_t OFF_EPOCH = OFF_BAR + 84 * 8;
constexpr uint32_t SMEM_BYTES = OFF_EPOCH + 16;

constexpr int FL_DONE = 0, FL_O = 1, FL_H = FL_O + 32, FL_Z = FL_H + 128, FL_COUNT = FL_Z + 64;

__device__ __align__(1024) bf16 g_o[kS * kD];
__device__ __align__(1024) bf16 g_h[kS * kF];
__device__ uint4 g_stats[kS];
__device__ uint4 g_csum[2 * 8 * 16 * 6];
__device__ uint4 g_halo[128 * 14 * 32];
__device__ unsigned g_flags[FL_COUNT * 8];

struct alignas(64) Maps {
  CUtensorMap x, wqkv_m, wqkv_r, w1_m, w1_r, wo_m, wo_r, w2_m, w2_r, o, h_ml, h_rl, cs_q, cs_1, xs, o_st, x32, out64, out32;
};

__device__ __forceinline__ uint32_t smem_u32(const void* p) { return (uint32_t)__cvta_generic_to_shared(p); }
__device__ __forceinline__ void mbar_init(uint32_t bar, uint32_t cnt) {
  asm volatile("mbarrier.init.shared::cta.b64 [%0], %1;" ::"r"(bar), "r"(cnt) : "memory");
}
__device__ __forceinline__ void mbar_expect_tx(uint32_t bar, uint32_t bytes) {
  asm volatile("mbarrier.arrive.expect_tx.shared::cta.b64 _, [%0], %1;" ::"r"(bar), "r"(bytes) : "memory");
}
__device__ __forceinline__ void mbar_arrive(uint32_t bar) {
  asm volatile("mbarrier.arrive.shared::cta.b64 _, [%0];" ::"r"(bar) : "memory");
}
#define FK_TRY "mbarrier.try_wait.parity.shared::cta.b64 p, [%0], %1;\n@p bra WAIT_DONE;\n"
__device__ __forceinline__ void mbar_wait(uint32_t bar, uint32_t parity) {
  asm volatile("{\n.reg .pred p;\n"
               "WAIT_LOOP:\n" FK_TRY
               "mbarrier.test_wait.parity.shared::cta.b64 p, [%0], %1;\n@!p bra WAIT_LOOP;\nWAIT_DONE:\n}"
               ::"r"(bar), "r"(parity) : "memory");
}
__device__ __forceinline__ void mbar_wait_long(uint32_t bar, uint32_t parity) {
  asm volatile("{\n.reg .pred p;\n.reg .u32 c;\nmov.u32 c, 0;\n"
               "WAIT_LOOP:\n" FK_TRY FK_TRY
               "add.u32 c, c, 1;\nsetp.lt.u32 p, c, 0x800000;\n@p bra WAIT_LOOP;\ntrap;\nWAIT_DONE:\n}"
               ::"r"(bar), "r"(parity) : "memory");
}
__device__ __forceinline__ bool elect_one() {
  uint32_t p;
  asm volatile("{\n.reg .pred q;\nelect.sync _|q, 0xffffffff;\nselp.u32 %0, 1, 0, q;\n}" : "=r"(p));
  return p != 0;
}
__device__ __forceinline__ void mbar_arrive_if(bool c, uint32_t bar) {
  asm volatile("{\n.reg .pred q;\nsetp.ne.u32 q, %1, 0;\n@q mbarrier.arrive.shared::cta.b64 _, [%0];\n}" ::"r"(bar), "r"((uint32_t)c) : "memory");
}
__device__ __forceinline__ unsigned ld_relaxed(const unsigned* p) {
  unsigned v;
  asm volatile("ld.relaxed.gpu.global.u32 %0, [%1];" : "=r"(v) : "l"(p) : "memory");
  return v;
}
__device__ __forceinline__ void flag_poll(int idx, unsigned target) {
  const unsigned* p = &g_flags[idx * 8];
  uint32_t spins = 0;
  while ((int)(ld_relaxed(p) - target) < 0) {
    __nanosleep(20);
    if (++spins > (1u << 22)) __trap();
  }
}
__device__ __forceinline__ void flag_release(int idx) {
  asm volatile("fence.acq_rel.gpu;\nfence.proxy.async;\nred.relaxed.gpu.global.add.u32 [%0], 1;" ::"l"(&g_flags[idx * 8]) : "memory");
}
__device__ __forceinline__ void flag_add(int idx) {
  asm volatile("red.relaxed.gpu.global.add.u32 [%0], 1;" ::"l"(&g_flags[idx * 8]) : "memory");
}
__device__ __forceinline__ void st_b128(uint4* p, uint32_t a, uint32_t b, uint32_t c, uint32_t d) {
  asm volatile("{\n.reg .b128 v;\n.reg .b64 lo, hi;\nmov.b64 lo, {%1, %2};\nmov.b64 hi, {%3, %4};\nmov.b128 v, {lo, hi};\n"
               "st.relaxed.gpu.global.b128 [%0], v;\n}" ::"l"(p), "r"(a), "r"(b), "r"(c), "r"(d) : "memory");
}
__device__ __forceinline__ uint4 ld_b128(const uint4* p) {
  uint4 r;
  asm volatile("{\n.reg .b128 v;\n.reg .b64 lo, hi;\nld.relaxed.gpu.global.b128 v, [%4];\nmov.b128 {lo, hi}, v;\n"
               "mov.b64 {%0, %1}, lo;\nmov.b64 {%2, %3}, hi;\n}"
               : "=r"(r.x), "=r"(r.y), "=r"(r.z), "=r"(r.w) : "l"(p) : "memory");
  return r;
}
__device__ __forceinline__ void ld_b128_if(uint4& v, const uint4* p, bool c) {
  asm volatile("{\n.reg .pred q;\n.reg .b128 t;\n.reg .b64 lo, hi;\nsetp.ne.u32 q, %5, 0;\n"
               "mov.b64 lo, {%0, %1};\nmov.b64 hi, {%2, %3};\nmov.b128 t, {lo, hi};\n"
               "@q ld.relaxed.gpu.global.b128 t, [%4];\n"
               "mov.b128 {lo, hi}, t;\nmov.b64 {%0, %1}, lo;\nmov.b64 {%2, %3}, hi;\n}"
               : "+r"(v.x), "+r"(v.y), "+r"(v.z), "+r"(v.w) : "l"(p), "r"((uint32_t)c) : "memory");
}
__device__ __forceinline__ uint4 ll_wait(const uint4* p, uint32_t tag, uint32_t mask = 0xffffffffu) {
  uint4 v = ld_b128(p);
  uint32_t spins = 0;
  while (!__all_sync(mask, v.w == tag)) {
    __nanosleep(20);
    v = ld_b128(p);
    if (++spins > (1u << 22)) __trap();
  }
  return v;
}
__device__ __forceinline__ void fence_async_all() { asm volatile("fence.proxy.async;" ::: "memory"); }
__device__ __forceinline__ void fence_async_smem() { asm volatile("fence.proxy.async.shared::cta;" ::: "memory"); }

__device__ __forceinline__ void tma2d(uint32_t dst, const CUtensorMap* m, int c0, int c1, uint32_t bar) {
  asm volatile("cp.async.bulk.tensor.2d.shared::cluster.global.mbarrier::complete_tx::bytes [%0], [%1, {%3, %4}], [%2];"
               ::"r"(dst), "l"(m), "r"(bar), "r"(c0), "r"(c1) : "memory");
}
__device__ __forceinline__ void tma3d(uint32_t dst, const CUtensorMap* m, int c0, int c1, int c2, uint32_t bar) {
  asm volatile("cp.async.bulk.tensor.3d.shared::cluster.global.mbarrier::complete_tx::bytes [%0], [%1, {%3, %4, %5}], [%2];"
               ::"r"(dst), "l"(m), "r"(bar), "r"(c0), "r"(c1), "r"(c2) : "memory");
}
__device__ __forceinline__ void tma2d_mc(uint32_t dst, const CUtensorMap* m, int c0, int c1, uint32_t bar) {
  asm volatile("cp.async.bulk.tensor.2d.shared::cluster.global.mbarrier::complete_tx::bytes.multicast::cluster [%0], [%1, {%3, %4}], [%2], %5;"
               ::"r"(dst), "l"(m), "r"(bar), "r"(c0), "r"(c1), "h"((uint16_t)3) : "memory");
}
__device__ __forceinline__ void tma3d_mc(uint32_t dst, const CUtensorMap* m, int c0, int c1, int c2, uint32_t bar) {
  asm volatile("cp.async.bulk.tensor.3d.shared::cluster.global.mbarrier::complete_tx::bytes.multicast::cluster [%0], [%1, {%3, %4, %5}], [%2], %6;"
               ::"r"(dst), "l"(m), "r"(bar), "r"(c0), "r"(c1), "r"(c2), "h"((uint16_t)3) : "memory");
}
__device__ __forceinline__ void mbar_arrive_cluster(uint32_t bar, uint32_t rank) {
  asm volatile("{\n.reg .b32 ra;\nmapa.shared::cluster.u32 ra, %0, %1;\nmbarrier.arrive.shared::cluster.b64 _, [ra];\n}"
               ::"r"(bar), "r"(rank) : "memory");
}
__device__ __forceinline__ void cluster_wait() { asm volatile("barrier.cluster.wait.acquire;" ::: "memory"); }
__device__ __forceinline__ void cluster_sync_tail() {
  asm volatile("barrier.cluster.arrive.relaxed.aligned;\nbarrier.cluster.wait.aligned;" ::: "memory");
}
__device__ __forceinline__ void cluster_sync() {
  asm volatile("barrier.cluster.arrive.release.aligned;\nbarrier.cluster.wait.acquire.aligned;" ::: "memory");
}
struct FSlice { int a0, r0; bool wide; };
__device__ __forceinline__ FSlice f_slice(int j) {
  const int s32 = (int)((0x2F28221B140D0600ull >> (8 * j)) & 0xFF);
  FSlice f;
  f.a0 = 32 * (s32 + (s32 & 1));
  f.r0 = (s32 & 1) ? 32 * s32 : 32 * s32 + 192;
  f.wide = (j != 0) && (j != 5);
  return f;
}
__device__ __forceinline__ void tma2d_store(const CUtensorMap* m, int c0, int c1, uint32_t src) {
  asm volatile("cp.async.bulk.tensor.2d.global.shared::cta.bulk_group [%0, {%2, %3}], [%1];"
               ::"l"(m), "r"(src), "r"(c0), "r"(c1) : "memory");
}
__device__ __forceinline__ void tma3d_store(const CUtensorMap* m, int c0, int c1, int c2, uint32_t src) {
  asm volatile("cp.async.bulk.tensor.3d.global.shared::cta.bulk_group [%0, {%2, %3, %4}], [%1];"
               ::"l"(m), "r"(src), "r"(c0), "r"(c1), "r"(c2) : "memory");
}
__device__ __forceinline__ void tma2d_add(const CUtensorMap* m, int c0, int c1, uint32_t src) {
  asm volatile("cp.reduce.async.bulk.tensor.2d.global.shared::cta.add.tile.bulk_group [%0, {%2, %3}], [%1];"
               ::"l"(m), "r"(src), "r"(c0), "r"(c1) : "memory");
}
__device__ __forceinline__ void prefetch_map(const CUtensorMap* m) {
  asm volatile("prefetch.tensormap [%0];" ::"l"(m) : "memory");
}
__device__ __forceinline__ void l2_prefetch(const void* p, uint32_t bytes) {
  asm volatile("cp.async.bulk.prefetch.L2.global [%0], %1;" ::"l"(p), "r"(bytes) : "memory");
}

__host__ __device__ constexpr uint32_t dlo(uint32_t off, uint32_t lbo) { return (off >> 4) + ((lbo >> 4) << 16); }
__host__ __device__ constexpr uint32_t dhi(uint32_t sbo, uint32_t mode) { return (sbo >> 4) | (mode << 30); }
constexpr uint32_t HI128 = dhi(1024, 1), HI64 = dhi(512, 2), HI32 = dhi(256, 3);
__device__ __forceinline__ void wg_fence() { asm volatile("wgmma.fence.sync.aligned;" ::: "memory"); }
__device__ __forceinline__ void wg_commit() { asm volatile("wgmma.commit_group.sync.aligned;" ::: "memory"); }
template <int N> __device__ __forceinline__ void wg_wait() {
  asm volatile("wgmma.wait_group.sync.aligned %0;" ::"n"(N) : "memory");
}
template <int T> __device__ __forceinline__ void fence_regs(float (&d)[T]) {
#pragma unroll
  for (int i = 0; i < T; i++) asm volatile("" : "+f"(d[i])::"memory");
}

template <int O, uint32_t AOFF, uint32_t AHI, uint32_t BOFF, uint32_t BHI, int T>
__device__ __forceinline__ void wgmma_n192(float (&d)[T], uint32_t abase, uint32_t bbase, int sc) {
  asm volatile("{\n.reg .pred p;\n.reg .b32 lo;\n.reg .b64 da, db;\n"
    "add.u32 lo, %96, %98;\nmov.b64 da, {lo, %99};\n"
    "add.u32 lo, %97, %100;\nmov.b64 db, {lo, %101};\n"
    "setp.ne.b32 p, %102, 0;\n"
    "wgmma.mma_async.sync.aligned.m64n192k16.f32.bf16.bf16 "
    "{%0, %1, %2, %3, %4, %5, %6, %7, %8, %9, %10, %11, %12, %13, %14, %15, %16, %17, %18, %19, %20, %21, %22, %23, %24, %25, %26, %27, %28, %29, %30, %31, %32, %33, %34, %35, %36, %37, %38, %39, %40, %41, %42, %43, %44, %45, %46, %47, %48, %49, %50, %51, %52, %53, %54, %55, %56, %57, %58, %59, %60, %61, %62, %63, %64, %65, %66, %67, %68, %69, %70, %71, %72, %73, %74, %75, %76, %77, %78, %79, %80, %81, %82, %83, %84, %85, %86, %87, %88, %89, %90, %91, %92, %93, %94, %95}, da, db, p, 1, 1, 0, 1;\n}\n"
    : "+f"(d[O + 0]), "+f"(d[O + 1]), "+f"(d[O + 2]), "+f"(d[O + 3]), "+f"(d[O + 4]), "+f"(d[O + 5]), "+f"(d[O + 6]), "+f"(d[O + 7]), "+f"(d[O + 8]), "+f"(d[O + 9]), "+f"(d[O + 10]), "+f"(d[O + 11]), "+f"(d[O + 12]), "+f"(d[O + 13]), "+f"(d[O + 14]), "+f"(d[O + 15]), "+f"(d[O + 16]), "+f"(d[O + 17]), "+f"(d[O + 18]), "+f"(d[O + 19]), "+f"(d[O + 20]), "+f"(d[O + 21]), "+f"(d[O + 22]), "+f"(d[O + 23]), "+f"(d[O + 24]), "+f"(d[O + 25]), "+f"(d[O + 26]), "+f"(d[O + 27]), "+f"(d[O + 28]), "+f"(d[O + 29]), "+f"(d[O + 30]), "+f"(d[O + 31]), "+f"(d[O + 32]), "+f"(d[O + 33]), "+f"(d[O + 34]), "+f"(d[O + 35]), "+f"(d[O + 36]), "+f"(d[O + 37]), "+f"(d[O + 38]), "+f"(d[O + 39]), "+f"(d[O + 40]), "+f"(d[O + 41]), "+f"(d[O + 42]), "+f"(d[O + 43]), "+f"(d[O + 44]), "+f"(d[O + 45]), "+f"(d[O + 46]), "+f"(d[O + 47]), "+f"(d[O + 48]), "+f"(d[O + 49]), "+f"(d[O + 50]), "+f"(d[O + 51]), "+f"(d[O + 52]), "+f"(d[O + 53]), "+f"(d[O + 54]), "+f"(d[O + 55]), "+f"(d[O + 56]), "+f"(d[O + 57]), "+f"(d[O + 58]), "+f"(d[O + 59]), "+f"(d[O + 60]), "+f"(d[O + 61]), "+f"(d[O + 62]), "+f"(d[O + 63]), "+f"(d[O + 64]), "+f"(d[O + 65]), "+f"(d[O + 66]), "+f"(d[O + 67]), "+f"(d[O + 68]), "+f"(d[O + 69]), "+f"(d[O + 70]), "+f"(d[O + 71]), "+f"(d[O + 72]), "+f"(d[O + 73]), "+f"(d[O + 74]), "+f"(d[O + 75]), "+f"(d[O + 76]), "+f"(d[O + 77]), "+f"(d[O + 78]), "+f"(d[O + 79]), "+f"(d[O + 80]), "+f"(d[O + 81]), "+f"(d[O + 82]), "+f"(d[O + 83]), "+f"(d[O + 84]), "+f"(d[O + 85]), "+f"(d[O + 86]), "+f"(d[O + 87]), "+f"(d[O + 88]), "+f"(d[O + 89]), "+f"(d[O + 90]), "+f"(d[O + 91]), "+f"(d[O + 92]), "+f"(d[O + 93]), "+f"(d[O + 94]), "+f"(d[O + 95])
    : "r"(abase), "r"(bbase), "n"(AOFF), "n"(AHI), "n"(BOFF), "n"(BHI), "r"(sc));
}

template <int O, uint32_t AOFF, uint32_t AHI, uint32_t BOFF, uint32_t BHI, int T>
__device__ __forceinline__ void wgmma_n48(float (&d)[T], uint32_t abase, uint32_t bbase, int sc) {
  asm volatile("{\n.reg .pred p;\n.reg .b32 lo;\n.reg .b64 da, db;\n"
    "add.u32 lo, %24, %26;\nmov.b64 da, {lo, %27};\n"
    "add.u32 lo, %25, %28;\nmov.b64 db, {lo, %29};\n"
    "setp.ne.b32 p, %30, 0;\n"
    "wgmma.mma_async.sync.aligned.m64n48k16.f32.bf16.bf16 "
    "{%0, %1, %2, %3, %4, %5, %6, %7, %8, %9, %10, %11, %12, %13, %14, %15, %16, %17, %18, %19, %20, %21, %22, %23}, da, db, p, 1, 1, 0, 1;\n}\n"
    : "+f"(d[O + 0]), "+f"(d[O + 1]), "+f"(d[O + 2]), "+f"(d[O + 3]), "+f"(d[O + 4]), "+f"(d[O + 5]), "+f"(d[O + 6]), "+f"(d[O + 7]), "+f"(d[O + 8]), "+f"(d[O + 9]), "+f"(d[O + 10]), "+f"(d[O + 11]), "+f"(d[O + 12]), "+f"(d[O + 13]), "+f"(d[O + 14]), "+f"(d[O + 15]), "+f"(d[O + 16]), "+f"(d[O + 17]), "+f"(d[O + 18]), "+f"(d[O + 19]), "+f"(d[O + 20]), "+f"(d[O + 21]), "+f"(d[O + 22]), "+f"(d[O + 23])
    : "r"(abase), "r"(bbase), "n"(AOFF), "n"(AHI), "n"(BOFF), "n"(BHI), "r"(sc));
}

template <int O, uint32_t AOFF, uint32_t AHI, uint32_t BOFF, uint32_t BHI, int T>
__device__ __forceinline__ void wgmma_n224(float (&d)[T], uint32_t abase, uint32_t bbase, int sc) {
  asm volatile("{\n.reg .pred p;\n.reg .b32 lo;\n.reg .b64 da, db;\n"
    "add.u32 lo, %112, %114;\nmov.b64 da, {lo, %115};\n"
    "add.u32 lo, %113, %116;\nmov.b64 db, {lo, %117};\n"
    "setp.ne.b32 p, %118, 0;\n"
    "wgmma.mma_async.sync.aligned.m64n224k16.f32.bf16.bf16 "
    "{%0, %1, %2, %3, %4, %5, %6, %7, %8, %9, %10, %11, %12, %13, %14, %15, %16, %17, %18, %19, %20, %21, %22, %23, %24, %25, %26, %27, %28, %29, %30, %31, %32, %33, %34, %35, %36, %37, %38, %39, %40, %41, %42, %43, %44, %45, %46, %47, %48, %49, %50, %51, %52, %53, %54, %55, %56, %57, %58, %59, %60, %61, %62, %63, %64, %65, %66, %67, %68, %69, %70, %71, %72, %73, %74, %75, %76, %77, %78, %79, %80, %81, %82, %83, %84, %85, %86, %87, %88, %89, %90, %91, %92, %93, %94, %95, %96, %97, %98, %99, %100, %101, %102, %103, %104, %105, %106, %107, %108, %109, %110, %111}, da, db, p, 1, 1, 0, 1;\n}\n"
    : "+f"(d[O + 0]), "+f"(d[O + 1]), "+f"(d[O + 2]), "+f"(d[O + 3]), "+f"(d[O + 4]), "+f"(d[O + 5]), "+f"(d[O + 6]), "+f"(d[O + 7]), "+f"(d[O + 8]), "+f"(d[O + 9]), "+f"(d[O + 10]), "+f"(d[O + 11]), "+f"(d[O + 12]), "+f"(d[O + 13]), "+f"(d[O + 14]), "+f"(d[O + 15]), "+f"(d[O + 16]), "+f"(d[O + 17]), "+f"(d[O + 18]), "+f"(d[O + 19]), "+f"(d[O + 20]), "+f"(d[O + 21]), "+f"(d[O + 22]), "+f"(d[O + 23]), "+f"(d[O + 24]), "+f"(d[O + 25]), "+f"(d[O + 26]), "+f"(d[O + 27]), "+f"(d[O + 28]), "+f"(d[O + 29]), "+f"(d[O + 30]), "+f"(d[O + 31]), "+f"(d[O + 32]), "+f"(d[O + 33]), "+f"(d[O + 34]), "+f"(d[O + 35]), "+f"(d[O + 36]), "+f"(d[O + 37]), "+f"(d[O + 38]), "+f"(d[O + 39]), "+f"(d[O + 40]), "+f"(d[O + 41]), "+f"(d[O + 42]), "+f"(d[O + 43]), "+f"(d[O + 44]), "+f"(d[O + 45]), "+f"(d[O + 46]), "+f"(d[O + 47]), "+f"(d[O + 48]), "+f"(d[O + 49]), "+f"(d[O + 50]), "+f"(d[O + 51]), "+f"(d[O + 52]), "+f"(d[O + 53]), "+f"(d[O + 54]), "+f"(d[O + 55]), "+f"(d[O + 56]), "+f"(d[O + 57]), "+f"(d[O + 58]), "+f"(d[O + 59]), "+f"(d[O + 60]), "+f"(d[O + 61]), "+f"(d[O + 62]), "+f"(d[O + 63]), "+f"(d[O + 64]), "+f"(d[O + 65]), "+f"(d[O + 66]), "+f"(d[O + 67]), "+f"(d[O + 68]), "+f"(d[O + 69]), "+f"(d[O + 70]), "+f"(d[O + 71]), "+f"(d[O + 72]), "+f"(d[O + 73]), "+f"(d[O + 74]), "+f"(d[O + 75]), "+f"(d[O + 76]), "+f"(d[O + 77]), "+f"(d[O + 78]), "+f"(d[O + 79]), "+f"(d[O + 80]), "+f"(d[O + 81]), "+f"(d[O + 82]), "+f"(d[O + 83]), "+f"(d[O + 84]), "+f"(d[O + 85]), "+f"(d[O + 86]), "+f"(d[O + 87]), "+f"(d[O + 88]), "+f"(d[O + 89]), "+f"(d[O + 90]), "+f"(d[O + 91]), "+f"(d[O + 92]), "+f"(d[O + 93]), "+f"(d[O + 94]), "+f"(d[O + 95]), "+f"(d[O + 96]), "+f"(d[O + 97]), "+f"(d[O + 98]), "+f"(d[O + 99]), "+f"(d[O + 100]), "+f"(d[O + 101]), "+f"(d[O + 102]), "+f"(d[O + 103]), "+f"(d[O + 104]), "+f"(d[O + 105]), "+f"(d[O + 106]), "+f"(d[O + 107]), "+f"(d[O + 108]), "+f"(d[O + 109]), "+f"(d[O + 110]), "+f"(d[O + 111])
    : "r"(abase), "r"(bbase), "n"(AOFF), "n"(AHI), "n"(BOFF), "n"(BHI), "r"(sc));
}

template <int O, uint32_t AOFF, uint32_t AHI, uint32_t BOFF, uint32_t BHI, int T>
__device__ __forceinline__ void wgmma_n160(float (&d)[T], uint32_t abase, uint32_t bbase, int sc) {
  asm volatile("{\n.reg .pred p;\n.reg .b32 lo;\n.reg .b64 da, db;\n"
    "add.u32 lo, %80, %82;\nmov.b64 da, {lo, %83};\n"
    "add.u32 lo, %81, %84;\nmov.b64 db, {lo, %85};\n"
    "setp.ne.b32 p, %86, 0;\n"
    "wgmma.mma_async.sync.aligned.m64n160k16.f32.bf16.bf16 "
    "{%0, %1, %2, %3, %4, %5, %6, %7, %8, %9, %10, %11, %12, %13, %14, %15, %16, %17, %18, %19, %20, %21, %22, %23, %24, %25, %26, %27, %28, %29, %30, %31, %32, %33, %34, %35, %36, %37, %38, %39, %40, %41, %42, %43, %44, %45, %46, %47, %48, %49, %50, %51, %52, %53, %54, %55, %56, %57, %58, %59, %60, %61, %62, %63, %64, %65, %66, %67, %68, %69, %70, %71, %72, %73, %74, %75, %76, %77, %78, %79}, da, db, p, 1, 1, 0, 1;\n}\n"
    : "+f"(d[O + 0]), "+f"(d[O + 1]), "+f"(d[O + 2]), "+f"(d[O + 3]), "+f"(d[O + 4]), "+f"(d[O + 5]), "+f"(d[O + 6]), "+f"(d[O + 7]), "+f"(d[O + 8]), "+f"(d[O + 9]), "+f"(d[O + 10]), "+f"(d[O + 11]), "+f"(d[O + 12]), "+f"(d[O + 13]), "+f"(d[O + 14]), "+f"(d[O + 15]), "+f"(d[O + 16]), "+f"(d[O + 17]), "+f"(d[O + 18]), "+f"(d[O + 19]), "+f"(d[O + 20]), "+f"(d[O + 21]), "+f"(d[O + 22]), "+f"(d[O + 23]), "+f"(d[O + 24]), "+f"(d[O + 25]), "+f"(d[O + 26]), "+f"(d[O + 27]), "+f"(d[O + 28]), "+f"(d[O + 29]), "+f"(d[O + 30]), "+f"(d[O + 31]), "+f"(d[O + 32]), "+f"(d[O + 33]), "+f"(d[O + 34]), "+f"(d[O + 35]), "+f"(d[O + 36]), "+f"(d[O + 37]), "+f"(d[O + 38]), "+f"(d[O + 39]), "+f"(d[O + 40]), "+f"(d[O + 41]), "+f"(d[O + 42]), "+f"(d[O + 43]), "+f"(d[O + 44]), "+f"(d[O + 45]), "+f"(d[O + 46]), "+f"(d[O + 47]), "+f"(d[O + 48]), "+f"(d[O + 49]), "+f"(d[O + 50]), "+f"(d[O + 51]), "+f"(d[O + 52]), "+f"(d[O + 53]), "+f"(d[O + 54]), "+f"(d[O + 55]), "+f"(d[O + 56]), "+f"(d[O + 57]), "+f"(d[O + 58]), "+f"(d[O + 59]), "+f"(d[O + 60]), "+f"(d[O + 61]), "+f"(d[O + 62]), "+f"(d[O + 63]), "+f"(d[O + 64]), "+f"(d[O + 65]), "+f"(d[O + 66]), "+f"(d[O + 67]), "+f"(d[O + 68]), "+f"(d[O + 69]), "+f"(d[O + 70]), "+f"(d[O + 71]), "+f"(d[O + 72]), "+f"(d[O + 73]), "+f"(d[O + 74]), "+f"(d[O + 75]), "+f"(d[O + 76]), "+f"(d[O + 77]), "+f"(d[O + 78]), "+f"(d[O + 79])
    : "r"(abase), "r"(bbase), "n"(AOFF), "n"(AHI), "n"(BOFF), "n"(BHI), "r"(sc));
}

__device__ __forceinline__ uint32_t pack_bf16(float lo, float hi) {
  uint32_t r;
  asm("cvt.rn.bf16x2.f32 %0, %1, %2;" : "=r"(r) : "f"(hi), "f"(lo));
  return r;
}
__device__ __forceinline__ float bf_lo(uint32_t v) { return __uint_as_float(v << 16); }
__device__ __forceinline__ float bf_hi(uint32_t v) { return __uint_as_float(v & 0xFFFF0000u); }
__device__ __forceinline__ void stsm4(uint32_t addr, uint32_t r0, uint32_t r1, uint32_t r2, uint32_t r3) {
  asm volatile("stmatrix.sync.aligned.m8n8.x4.shared.b16 [%0], {%1, %2, %3, %4};"
               ::"r"(addr), "r"(r0), "r"(r1), "r"(r2), "r"(r3) : "memory");
}
__device__ __forceinline__ void ldsm4(uint32_t (&r)[4], uint32_t addr) {
  asm volatile("ldmatrix.sync.aligned.m8n8.x4.shared.b16 {%0, %1, %2, %3}, [%4];"
               : "=r"(r[0]), "=r"(r[1]), "=r"(r[2]), "=r"(r[3]) : "r"(addr) : "memory");
}
__device__ __forceinline__ void ldsm4t(uint32_t (&r)[4], uint32_t addr) {
  asm volatile("ldmatrix.sync.aligned.m8n8.x4.trans.shared.b16 {%0, %1, %2, %3}, [%4];"
               : "=r"(r[0]), "=r"(r[1]), "=r"(r[2]), "=r"(r[3]) : "r"(addr) : "memory");
}
__device__ __forceinline__ void mma16816(float (&c)[4], uint32_t a0, uint32_t a1, uint32_t a2, uint32_t a3,
                                         uint32_t b0, uint32_t b1) {
  asm volatile("mma.sync.aligned.m16n8k16.row.col.f32.bf16.bf16.f32 {%0,%1,%2,%3}, {%4,%5,%6,%7}, {%8,%9}, {%0,%1,%2,%3};"
               : "+f"(c[0]), "+f"(c[1]), "+f"(c[2]), "+f"(c[3])
               : "r"(a0), "r"(a1), "r"(a2), "r"(a3), "r"(b0), "r"(b1));
}
__device__ __forceinline__ void mma16816_z(float (&c)[4], uint32_t a0, uint32_t a1, uint32_t a2, uint32_t a3,
                                           uint32_t b0, uint32_t b1) {
  asm volatile("mma.sync.aligned.m16n8k16.row.col.f32.bf16.bf16.f32 {%0,%1,%2,%3}, {%4,%5,%6,%7}, {%8,%9}, {%10,%10,%10,%10};"
               : "=f"(c[0]), "=f"(c[1]), "=f"(c[2]), "=f"(c[3])
               : "r"(a0), "r"(a1), "r"(a2), "r"(a3), "r"(b0), "r"(b1), "f"(0.f));
}
__device__ __forceinline__ void mma1688(float (&c)[4], uint32_t a0, uint32_t a1, uint32_t b0) {
  asm volatile("mma.sync.aligned.m16n8k8.row.col.f32.bf16.bf16.f32 {%0,%1,%2,%3}, {%4,%5}, {%6}, {%0,%1,%2,%3};"
               : "+f"(c[0]), "+f"(c[1]), "+f"(c[2]), "+f"(c[3])
               : "r"(a0), "r"(a1), "r"(b0));
}
__device__ __forceinline__ float ex2(float x) {
  float y;
  asm("ex2.approx.ftz.f32 %0, %1;" : "=f"(y) : "f"(x));
  return y;
}
__device__ __forceinline__ float tanh_fast(float x) {
  float y;
  asm("tanh.approx.f32 %0, %1;" : "=f"(y) : "f"(x));
  return y;
}
__device__ __forceinline__ float2 lds64f(uint32_t addr) {
  float2 v;
  asm volatile("ld.shared.v2.f32 {%0, %1}, [%2];" : "=f"(v.x), "=f"(v.y) : "r"(addr));
  return v;
}

#define PROF(slot)
#define PROFW(slot)
#define GT(slot)
#define INTRA(k)
#define INTRAN()
#define STEPT(k)
#define LAT(k, e)
#define TBEG()
#define TEND(var)

struct Attn {
  float s[2][4][4];
  uint32_t p[2][4][2];
  float ilo[2], ihi[2];
};
template <int H> struct HeadTile { static constexpr int T0 = (H == 0) ? 0 : (H == 1) ? 2 : (H == 2) ? 5 : 7; };

template <int H>
__device__ __forceinline__ void attn_scores(Attn& st, const uint32_t (&qp)[10][2], uint32_t kv, uint32_t kv2, int tq) {
  constexpr int T0 = HeadTile<H>::T0;
  uint32_t ka[2][4], kc[2][4], ks[4];
#pragma unroll
  for (int kp = 0; kp < 2; kp++) {
    ldsm4(ka[kp], kv2 + kp * 16 * KV_PITCH + T0 * 16);
    ldsm4(kc[kp], kv2 + kp * 16 * KV_PITCH + (T0 + 3) * 16);
  }
  ldsm4(ks, kv + (T0 + 2) * 16);
  const uint32_t sa0 = tq < 2 ? qp[T0 + 2][0] : 0u, sa1 = tq < 2 ? qp[T0 + 2][1] : 0u;
  const uint32_t sb0 = tq < 2 ? 0u : qp[T0 + 2][0], sb1 = tq < 2 ? 0u : qp[T0 + 2][1];
#pragma unroll
  for (int kt = 0; kt < 4; kt++) {
    mma16816_z(st.s[0][kt], qp[T0][0], qp[T0][1], qp[T0 + 1][0], qp[T0 + 1][1], ka[kt >> 1][2 * (kt & 1)], ka[kt >> 1][2 * (kt & 1) + 1]);
    mma16816_z(st.s[1][kt], qp[T0 + 3][0], qp[T0 + 3][1], qp[T0 + 4][0], qp[T0 + 4][1], kc[kt >> 1][2 * (kt & 1)], kc[kt >> 1][2 * (kt & 1) + 1]);
  }
#pragma unroll
  for (int kt = 0; kt < 4; kt++) {
    mma1688(st.s[0][kt], sa0, sa1, ks[kt]);
    mma1688(st.s[1][kt], sb0, sb1, ks[kt]);
  }
}

__device__ __forceinline__ void attn_softmax(Attn& sa, Attn& sb2, uint32_t vmask, int e) {
  float lo[4][4], hi[4][4], mlo[4], mhi[4], slo[4], shi[4];
  const float ninf = __int_as_float(0xff800000);
#pragma unroll
  for (int h = 0; h < 4; h++) {
    const Attn& st = h < 2 ? sa : sb2;
#pragma unroll
    for (int kt = 0; kt < 4; kt++) {
      const float vlo = e ? st.s[h & 1][kt][1] : st.s[h & 1][kt][0];
      const float vhi = e ? st.s[h & 1][kt][3] : st.s[h & 1][kt][2];
      lo[h][kt] = ((vmask >> kt) & 1) ? vlo : ninf;
      hi[h][kt] = ((vmask >> (4 + kt)) & 1) ? vhi : ninf;
    }
  }
#pragma unroll
  for (int h = 0; h < 4; h++) {
    mlo[h] = fmaxf(fmaxf(lo[h][0], lo[h][1]), fmaxf(lo[h][2], lo[h][3]));
    mhi[h] = fmaxf(fmaxf(hi[h][0], hi[h][1]), fmaxf(hi[h][2], hi[h][3]));
  }
#pragma unroll
  for (int o = 1; o <= 2; o <<= 1)
#pragma unroll
    for (int h = 0; h < 4; h++) {
      mlo[h] = fmaxf(mlo[h], __shfl_xor_sync(0xffffffffu, mlo[h], o));
      mhi[h] = fmaxf(mhi[h], __shfl_xor_sync(0xffffffffu, mhi[h], o));
    }
  const uint32_t sel0 = e ? 0x1044 : 0x4410, sel1 = e ? 0x3244 : 0x4432;
#pragma unroll
  for (int h = 0; h < 4; h++) {
    Attn& st = h < 2 ? sa : sb2;
    float pl[4], ph[4];
#pragma unroll
    for (int kt = 0; kt < 4; kt++) { pl[kt] = ex2(lo[h][kt] - mlo[h]); ph[kt] = ex2(hi[h][kt] - mhi[h]); }
    slo[h] = (pl[0] + pl[1]) + (pl[2] + pl[3]);
    shi[h] = (ph[0] + ph[1]) + (ph[2] + ph[3]);
#pragma unroll
    for (int kt = 0; kt < 4; kt++) {
      const uint32_t pk = pack_bf16(pl[kt], ph[kt]);
      st.p[h & 1][kt][0] = __byte_perm(pk, 0, sel0);
      st.p[h & 1][kt][1] = __byte_perm(pk, 0, sel1);
    }
  }
#pragma unroll
  for (int o = 1; o <= 2; o <<= 1)
#pragma unroll
    for (int h = 0; h < 4; h++) {
      slo[h] += __shfl_xor_sync(0xffffffffu, slo[h], o);
      shi[h] += __shfl_xor_sync(0xffffffffu, shi[h], o);
    }
#pragma unroll
  for (int h = 0; h < 4; h++) {
    Attn& st = h < 2 ? sa : sb2;
    st.ilo[h & 1] = __fdividef(1.f, slo[h]);
    st.ihi[h & 1] = __fdividef(1.f, shi[h]);
  }
}

template <int H>
__device__ __forceinline__ void attn_values(const Attn& st, uint32_t (&op)[10][2], uint32_t kv, int tq) {
  constexpr int T0 = HeadTile<H>::T0;
  uint32_t vb[5][4];
#pragma unroll
  for (int dt = 0; dt < 5; dt++) ldsm4t(vb[dt], kv + 160 + (T0 + dt) * 16);
  float o[2][3][4];
#pragma unroll
  for (int h = 0; h < 2; h++)
#pragma unroll
    for (int dt = 0; dt < 3; dt++)
      mma16816_z(o[h][dt], st.p[h][0][0], st.p[h][0][1], st.p[h][1][0], st.p[h][1][1], vb[2 * h + dt][0], vb[2 * h + dt][1]);
#pragma unroll
  for (int h = 0; h < 2; h++)
#pragma unroll
    for (int dt = 0; dt < 3; dt++)
      mma16816(o[h][dt], st.p[h][2][0], st.p[h][2][1], st.p[h][3][0], st.p[h][3][1], vb[2 * h + dt][2], vb[2 * h + dt][3]);
#pragma unroll
  for (int t = 0; t < 5; t++) {
    const int h = t < 2 ? 0 : 1, dt = t < 2 ? t : t - 2;
    float v0 = o[h][dt][0] * st.ilo[h], v1 = o[h][dt][1] * st.ilo[h], v2 = o[h][dt][2] * st.ihi[h], v3 = o[h][dt][3] * st.ihi[h];
    if (t == 2 && tq < 2) {
      v0 = o[0][2][0] * st.ilo[0]; v1 = o[0][2][1] * st.ilo[0]; v2 = o[0][2][2] * st.ihi[0]; v3 = o[0][2][3] * st.ihi[0];
    }
    op[T0 + t][0] = pack_bf16(v0, v1);
    op[T0 + t][1] = pack_bf16(v2, v3);
  }
}

__device__ __forceinline__ uint32_t h_stage_addr(uint32_t sb, int t, int w, int wq, int lane) {
  const int m = lane >> 3;
  const int row = 16 * wq + (m & 1) * 8 + (lane & 7);
  if (t < 24) {
    const int chunk = (t & 7) + (m >> 1);
    return sb + OFF_STG + (t >> 3) * 16384 + w * 8192 + row * 128 + ((chunk ^ (row & 7)) << 4);
  }
  const int chunk = (t - 24) + (m >> 1);
  return sb + OFF_STG + 49152 + w * 4096 + row * 64 + ((chunk ^ ((row >> 1) & 3)) << 4);
}

__device__ __forceinline__ uint32_t fma2(uint32_t a, uint32_t b, uint32_t c) {
  uint32_t d;
  asm volatile("fma.rn.bf16x2 %0, %1, %2, %3;" : "=r"(d) : "r"(a), "r"(b), "r"(c));
  return d;
}
__device__ __forceinline__ uint32_t mul2(uint32_t a, uint32_t b) {
  uint32_t d;
  asm volatile("mul.rn.bf16x2 %0, %1, %2;" : "=r"(d) : "r"(a), "r"(b));
  return d;
}
__device__ __forceinline__ uint32_t tanh2(uint32_t a) {
  uint32_t d;
  asm volatile("tanh.approx.bf16x2 %0, %1;" : "=r"(d) : "r"(a));
  return d;
}
__device__ __forceinline__ uint32_t gelu2(uint32_t hp) {
  const uint32_t K0 = 0x3FCC3FCCu, K1 = 0x3E923E92u;
  const uint32_t u = mul2(hp, fma2(mul2(hp, hp), K1, K0));
  return fma2(hp, tanh2(u), hp);
}
struct GeluAddr { uint32_t row128, x128, row64, x64, cb; };
struct GeluStage { uint32_t hp[4], u[4]; };
struct GeluConst { uint32_t b0, b1; };
template <int T>
__device__ __forceinline__ void gelu_ld(GeluConst& k, const GeluAddr& a) {
  asm volatile("ld.shared.u32 %0, [%1 + %2];" : "=r"(k.b0) : "r"(a.cb), "n"(T * 16));
  asm volatile("ld.shared.u32 %0, [%1 + %2];" : "=r"(k.b1) : "r"(a.cb), "n"(T * 16 + 16));
}
template <int T>
__device__ __forceinline__ void gelu_arg(GeluStage& st, const GeluConst& k, const uint32_t (&hc)[56], uint32_t chl,
                                         uint32_t chh) {
  const uint32_t K0 = 0x3FCC3FCCu, K1 = 0x3E923E92u;
  st.hp[0] = fma2(hc[2 * T], chl, k.b0);
  st.hp[1] = fma2(hc[2 * T + 1], chh, k.b0);
  st.hp[2] = fma2(hc[2 * T + 2], chl, k.b1);
  st.hp[3] = fma2(hc[2 * T + 3], chh, k.b1);
#pragma unroll
  for (int i = 0; i < 4; i++) st.u[i] = mul2(st.hp[i], fma2(mul2(st.hp[i], st.hp[i]), K1, K0));
}
template <int T>
__device__ __forceinline__ void gelu_out(const GeluStage& st, const GeluAddr& a) {
  const uint32_t addr = (T < 24) ? a.row128 + (T >> 3) * 16384 + (a.x128 ^ ((T & 7) << 4)) : a.row64 + (a.x64 ^ ((T - 24) << 4));
  uint32_t r[4];
#pragma unroll
  for (int i = 0; i < 4; i++) r[i] = fma2(st.hp[i], tanh2(st.u[i]), st.hp[i]);
  stsm4(addr, r[0], r[1], r[2], r[3]);
}

template <int I> struct IC { static constexpr int v = I; };

template <int B, int E, class F> __device__ __forceinline__ void static_for(F&& f) {
  if constexpr (B < E) { f(IC<B>{}); static_for<B + 1, E>(f); }
}

struct Ring {
  uint32_t slot, phase;
  template <uint32_t N> __device__ __forceinline__ void next() {
    if (++slot == N) { slot = 0; phase ^= 1; }
  }
};

__global__ void __launch_bounds__(kThreads, 1)
fused_kernel(const __grid_constant__ Maps maps, const bf16* __restrict__ x, const bf16* __restrict__ wqkv,
             const bf16* __restrict__ wo, const bf16* __restrict__ w1, const bf16* __restrict__ b1,
             const bf16* __restrict__ w2, const bf16* __restrict__ b2, bf16* __restrict__ out) {
  extern __shared__ __align__(1024) uint8_t smem[];
  GT(22);
  const uint32_t sb = smem_u32(smem);
  const int tid = threadIdx.x, lane = tid & 31;
  const int warp = __shfl_sync(0xffffffffu, tid >> 5, 0);
  const int cta = blockIdx.x;
  const int rank = cta & 1, cl = cta >> 1;
  const int tj = cl >> 3, ti = 2 * (cl & 7) + rank;
  const int me = ti * 8 + tj;
  const int nt = tj & 3, kh = tj >> 2;
  auto bar = [&](uint32_t idx) { return sb + OFF_BAR + idx * 8; };

  {
    const FSlice f0 = f_slice(tj);
    const bf16* pa;
    if (tid < 256) {
      pa = x + (size_t)(128 * ti + (tid & 127)) * kD + 64 * (tid >> 7);
    } else {
      const int r = (tid - 256) >> 2, c = tid & 3;
      pa = w1 + (size_t)(32 * (r >> 4) + 16 * rank + (r & 15)) * kF + (c < 3 ? f0.a0 + 64 * c : f0.r0);
    }
    asm volatile("prefetch.global.L2 [%0];" ::"l"(pa) : "memory");
  }
  if (tid == 256) prefetch_map(&maps.x);
  if (tid == 288) { prefetch_map(&maps.w1_m); prefetch_map(&maps.w1_r); }
  if (lane == 0) {
    if (sb & 1023) __trap();
#pragma unroll
    for (int u = 0; u < 7; u++) {
      const int i = warp * 7 + u;
      const bool eight = (i >= BAR_A_EMPTY && i < BAR_B_FULL) || (i >= BAR_B_EMPTY && i < BAR_B_PEER) ||
                         (i >= BAR_B2_EMPTY && i < BAR_B2_PEER) || i == BAR_PROL || i == BAR_PROL2 || i == BAR_KV ||
                         i == BAR_O_W || i == BAR_ATT || i == BAR_XROWS || i == BAR_ROWP || (i >= BAR_HT0 && i <= BAR_DONE);
      mbar_init(bar(i), eight ? 8 : 1);
    }
    asm volatile("fence.mbarrier_init.release.cluster;" ::: "memory");
    fence_async_smem();
  }
  __syncthreads();
  asm volatile("barrier.cluster.arrive.relaxed.aligned;" ::: "memory");
  const FSlice fs = f_slice(tj);
  const bool jodd = tj & 1, nodd = nt & 1;
  const int qmain = 80 * tj + (jodd ? 16 : 0), qrem = 80 * tj + (jodd ? 0 : 64);
  const int omain = 160 * nt + (nodd ? 32 : 0), orem = 160 * nt + (nodd ? 0 : 128);

  if (warp >= 8) {
    asm volatile("setmaxnreg.dec.sync.aligned.u32 56;");
    if (warp == 8) {
      {
        PROF(0);
        Ring r{0, 1};
        auto put = [&](const CUtensorMap* m, int c0, int c1, uint32_t bytes) {
          mbar_wait_long(bar(BAR_A_EMPTY + r.slot), r.phase);
          if (elect_one()) {
            mbar_expect_tx(bar(BAR_A_FULL + r.slot), bytes);
            tma2d(sb + OFF_A + r.slot * A_SLOT, m, c0, c1, bar(BAR_A_FULL + r.slot));
          }
          r.next<A_N>();
        };
#pragma unroll 1
        for (int it = 0; it < 20; it++) put(&maps.x, 64 * (it < 10 ? it : it - 10), 128 * ti, 16384);
#pragma unroll 1
        for (int s = 0; s < 4; s++) {
          if (s == 0) mbar_wait_long(bar(BAR_H_ST0), 0);
          if (s == 1) mbar_wait_long(bar(BAR_H_RDY), 0);
          if (s == 0) PROF(2);
          const FSlice f2 = f_slice(4 * kh + ((nt + s) & 3));
#pragma unroll 1
          for (int t = 0; t < 3; t++) put(&maps.h_ml, f2.a0 + 64 * t, 128 * ti, 16384);
          if (f2.wide) put(&maps.h_rl, f2.r0, 128 * ti, 8192);
        }
        mbar_wait_long(bar(BAR_O_RDY), 0);
        PROF(1);
#pragma unroll 1
        for (int t = 0; t < 5; t++) put(&maps.o, 320 * kh + 64 * t, 128 * ti, 16384);
      }
    } else if (warp == 9) {
      {
        cluster_wait();
        Ring r{0, 1};
        const uint32_t half = sb + OFF_B + rank * 8192;
        const int k16 = 16 * rank;
        auto wait_free = [&]() {
          mbar_wait_long(bar(BAR_B_EMPTY + r.slot), r.phase);
          mbar_wait_long(bar(BAR_B_PEER + r.slot), r.phase);
        };
#pragma unroll 1
        for (int q = 0; q < 20; q++) {
          wait_free();
          if (elect_one()) {
            const uint32_t dst = half + r.slot * B_SLOT, fb = bar(BAR_B_FULL + r.slot);
            mbar_expect_tx(fb, fs.wide ? 14336 : 12288);
            tma3d_mc(dst, &maps.w1_m, fs.a0, 32 * q + k16, 0, fb);
            if (fs.wide) tma2d_mc(dst + 6144, &maps.w1_r, fs.r0, 32 * q + k16, fb);
            if (q == 8) {
              l2_prefetch((const char*)wo + cta * 6400, 6400);
              l2_prefetch((const char*)w2 + cta * 17280, 17280);
            }
          }
          r.next<B_N>();
        }
#pragma unroll 1
        for (int q = 0; q < 20; q++) {
          wait_free();
          if (elect_one()) {
            const uint32_t dst = half + r.slot * B_SLOT, fb = bar(BAR_B_FULL + r.slot);
            mbar_expect_tx(fb, 15360);
            tma3d_mc(dst, &maps.wqkv_m, qmain, 32 * q + k16, 0, fb);
            tma3d_mc(dst + 6144, &maps.wqkv_r, qrem, 32 * q + k16, 0, fb);
          }
          r.next<B_N>();
        }
        const uint32_t half2 = sb + OFF_B + rank * 6144;
        int u = 0;
        auto put2 = [&](const CUtensorMap* mm, const CUtensorMap* mr, int krow) {
          if (u < 7 && u != 1 && u != 5) {
            wait_free();
            r.next<B_N>();
            if (u == 0) { wait_free(); r.next<B_N>(); }
          }
          const uint32_t v = u & 7, par = ((u >> 3) & 1) ^ 1;
          mbar_wait_long(bar(BAR_B2_EMPTY + v), par);
          mbar_wait_long(bar(BAR_B2_PEER + v), par);
          if (elect_one()) {
            const uint32_t dst = half2 + ((v + 6) & 7) * B2_SLOT, fb = bar(BAR_B2_FULL + v);
            mbar_expect_tx(fb, 10240);
            tma3d_mc(dst, mm, omain, krow + k16, 0, fb);
            tma2d_mc(dst + 4096, mr, orem, krow + k16, fb);
          }
          u++;
        };
#pragma unroll 1
        for (int s = 0; s < 4; s++) {
          const FSlice f2 = f_slice(4 * kh + ((nt + s) & 3));
#pragma unroll 1
          for (int q = 0; q < 6; q++) put2(&maps.w2_m, &maps.w2_r, f2.a0 + 32 * q);
          if (f2.wide) put2(&maps.w2_m, &maps.w2_r, f2.r0);
        }
#pragma unroll 1
        for (int q = 0; q < 10; q++) put2(&maps.wo_m, &maps.wo_r, 320 * kh + 32 * q);
      }
    } else if (warp == 10) {
      unsigned ep = 0;
      if (lane == 0) {
        ep = *(volatile unsigned*)&g_flags[FL_DONE * 8] / kCtas + 1;
        *(volatile unsigned*)(smem + OFF_EPOCH) = ep;
        mbar_arrive(bar(BAR_EPOCH));
        atomicAdd(&g_flags[FL_DONE * 8], 1u);
        mbar_wait_long(bar(BAR_GO), 0);
        const bool has1 = ti < (fs.wide ? 14 : 12);
        mbar_expect_tx(bar(BAR_CS_FULL), (has1 ? 20480 : 0) + 20480);
#pragma unroll 1
        for (int q = 0; q < 5; q++) tma2d(sb + OFF_STG + 20480 + q * 4096, &maps.xs, 128 * q, 128 * ti + 16 * tj, bar(BAR_CS_FULL));
        if (has1) {
          const int col = ti < 12 ? fs.a0 + 16 * ti : fs.r0 + 16 * (ti - 12);
#pragma unroll 1
          for (int q = 0; q < 4; q++) tma2d(sb + OFF_STG + q * 5120, &maps.cs_1, col, 160 * q, bar(BAR_CS_FULL));
        }
      }
      ep = __shfl_sync(0xffffffffu, ep, 0);
#pragma unroll
      for (int u = 0; u < 4; u++) {
        const int i2 = lane + 32 * u;
        const int c = 2 * i2;
        const int col = c < 192 ? fs.a0 + c : fs.r0 + c - 192;
        if (i2 < 112)
          *(uint32_t*)(smem + OFF_B1 + i2 * 4) = (c < 192 || fs.wide) ? mul2(__ldg((const uint32_t*)(b1 + col)), 0x3F003F00u) : 0u;
      }
      {
#pragma unroll
        for (int u = 0; u < 2; u++) {
          const int i2 = lane + 32 * u, t = i2 >> 2;
          if (i2 < 40) {
            const int col = (t < 6 ? omain + 80 * kh + 8 * t : (kh ? orem : omain + 48) + 8 * (t - 6)) + 2 * (i2 & 3);
            *(uint32_t*)(smem + OFF_B2 + i2 * 4) = __ldg((const uint32_t*)(b2 + col));
          }
        }
      }
      auto publish_sums = [&](int which, uint32_t src) {
        const float4* p = (const float4*)(smem + src) + (lane & 3) + (lane >> 2) * 64;
        float4 s = make_float4(0.f, 0.f, 0.f, 0.f);
#pragma unroll
        for (int k0 = 0; k0 < 16; k0 += 8) {
          float4 v[8];
#pragma unroll
          for (int k = 0; k < 8; k++) v[k] = p[(k0 + k) * 4];
#pragma unroll
          for (int d = 4; d > 0; d >>= 1)
#pragma unroll
            for (int k = 0; k < d; k++) { v[k].x += v[k + d].x; v[k].y += v[k + d].y; v[k].z += v[k + d].z; v[k].w += v[k + d].w; }
          s.x += v[0].x; s.y += v[0].y; s.z += v[0].z; s.w += v[0].w;
        }
#pragma unroll
        for (int o = 4; o < 32; o <<= 1) {
          s.x += __shfl_xor_sync(0xffffffffu, s.x, o); s.y += __shfl_xor_sync(0xffffffffu, s.y, o);
          s.z += __shfl_xor_sync(0xffffffffu, s.z, o); s.w += __shfl_xor_sync(0xffffffffu, s.w, o);
        }
        float a[3];
#pragma unroll
        for (int i2 = 0; i2 < 3; i2++) {
          const int c = min(3 * lane + i2, 15), from = c >> 2, comp = c & 3;
          const float vx = __shfl_sync(0xffffffffu, s.x, from), vy = __shfl_sync(0xffffffffu, s.y, from);
          const float vz = __shfl_sync(0xffffffffu, s.z, from), vw = __shfl_sync(0xffffffffu, s.w, from);
          a[i2] = comp == 0 ? vx : comp == 1 ? vy : comp == 2 ? vz : vw;
        }
        if (lane < 6)
          st_b128(&g_csum[((which * 8 + tj) * 16 + ti) * 6 + lane], __float_as_uint(a[0]), __float_as_uint(a[1]),
                  __float_as_uint(a[2]), ep);
      };
      auto gather_sums = [&](int which, int npiece, float* dst) {
        const uint4* src = &g_csum[(which * 8 + tj) * 16 * 6];
        uint4 v[3];
        uint32_t spins = 0;
        while (true) {
          bool ok = true;
#pragma unroll
          for (int u = 0; u < 3; u++) {
            v[u] = ld_b128(src + min(lane + 32 * u, npiece * 6 - 1));
            ok = ok && v[u].w == ep;
          }
          if (__all_sync(0xffffffffu, ok)) break;
          __nanosleep(20);
          if (++spins > (1u << 22)) __trap();
        }
#pragma unroll
        for (int u = 0; u < 3; u++) {
          const int i2 = min(lane + 32 * u, npiece * 6 - 1);
          const int piece = i2 / 6, p = i2 - 6 * piece;
          float* d = dst + 16 * piece + 3 * p;
          d[0] = __uint_as_float(v[u].x);
          if (p < 5) { d[1] = __uint_as_float(v[u].y); d[2] = __uint_as_float(v[u].z); }
        }
        __syncwarp();
      };
      if (lane == 0) {
        mbar_wait_long(bar(BAR_XROWS), 0);
        if (ti < 15) {
          const int col = ti < 12 ? 640 * (ti >> 2) + qmain + 16 * (ti & 3) : 640 * (ti - 12) + qrem;
          mbar_expect_tx(bar(BAR_CS2_FULL), 20480);
#pragma unroll 1
          for (int q = 0; q < 4; q++) tma2d(sb + OFF_STG + 20480 + q * 5120, &maps.cs_q, col, 160 * q, bar(BAR_CS2_FULL));
        } else {
          mbar_arrive(bar(BAR_CS2_FULL));
        }
      }
      __syncwarp();
      PROF(10);
      mbar_wait_long(bar(BAR_PROL), 0);
      PROF(11);
      publish_sums(0, OFF_COLP);
      if (lane == 0) mbar_arrive(bar(BAR_COLC));
      PROF(8);
      mbar_wait_long(bar(BAR_ROWP), 0);
      PROF(9);
      {
        const float* rp = (const float*)(smem + OFF_ROWP);
        float4 v[8];
#pragma unroll
        for (int k = 0; k < 8; k++) v[k] = *(const float4*)(rp + lane * 32 + ((k + lane) & 7) * 4);
#pragma unroll
        for (int d = 4; d > 0; d >>= 1)
#pragma unroll
          for (int k = 0; k < d; k++) { v[k].x += v[k + d].x; v[k].y += v[k + d].y; v[k].z += v[k + d].z; v[k].w += v[k + d].w; }
        const float s = (v[0].x + v[0].y) + (v[0].z + v[0].w), other = __shfl_xor_sync(0xffffffffu, s, 1);
        const float md = ((lane & 1) ? other : s) * (1.f / kD), m2 = ((lane & 1) ? s : other) * (1.f / kD);
        const float var = fmaxf(m2 - md * md, 0.f), mean = rp[1024 + (lane >> 1)] + md;
        const float rstd = rsqrtf(var + 1e-5f);
        const float var2 = var * rstd * rstd;
        const float rs = rstd * rsqrtf(var2 + 1e-5f);
        if ((lane & 1) == 0)
          st_b128(&g_stats[128 * ti + 16 * tj + (lane >> 1)], __float_as_uint(rstd), __float_as_uint(mean), __float_as_uint(rs), ep);
      }
      PROF(7);
      gather_sums(0, 14, (float*)(smem + OFF_C1));
      PROF(12);
      if (lane == 0) { mbar_arrive(bar(BAR_AUX)); PROF(13); }
      mbar_wait_long(bar(BAR_PROL2), 0);
      publish_sums(1, OFF_STG + 49152);
      gather_sums(1, 15, (float*)(smem + OFF_C));
      if (lane == 0) mbar_arrive(bar(BAR_AUX2));
      if (lane == 0) {
#pragma unroll 1
        for (int T = 0; T < 4; T++) {
          mbar_wait_long(bar(BAR_HT0 + T), 0);
          if (T < 3) tma2d_store(&maps.h_ml, fs.a0 + 64 * T, 128 * ti, sb + OFF_STG + T * 16384);
          else if (fs.wide) tma2d_store(&maps.h_rl, fs.r0, 128 * ti, sb + OFF_STG + 49152);
        }
        asm volatile("cp.async.bulk.commit_group;" ::: "memory");
        asm volatile("cp.async.bulk.wait_group 0;" ::: "memory");
        mbar_arrive(bar(BAR_HDONE));
        mbar_arrive(bar(BAR_H_ST0));
        flag_add(FL_H + ti * 8 + tj);
        PROF(6);
      }
      __syncwarp();
      if (lane < 4) flag_poll(FL_H + ti * 8 + 4 * kh + lane, ep);
      __syncwarp();
      if (lane == 0) { mbar_arrive(bar(BAR_H_RDY)); PROF(3); }
      {
#pragma unroll 4
        for (int i2 = lane; i2 < 1280; i2 += 32) {
          const int r = i2 / 10, c = i2 - 10 * r;
          const int col = c < 6 ? omain + 80 * kh + 8 * c : (kh ? orem : omain + 48) + 8 * (c - 6);
          __stcg((uint4*)(out + (size_t)(128 * ti + r) * kD + col), make_uint4(0, 0, 0, 0));
        }
        __syncwarp();
        if (lane == 0)
          asm volatile("fence.acq_rel.gpu;\nfence.proxy.async;\nred.relaxed.gpu.global.add.u32 [%0], 1;"
                       ::"l"(&g_flags[(FL_Z + ti * 4 + nt) * 8]) : "memory");
      }
      if (lane == 0) {
        mbar_wait_long(bar(BAR_ATT), 0);
        mbar_expect_tx(bar(BAR_XR), 16384 + 8192);
        tma2d(sb + OFF_XR, &maps.x, omain + 80 * kh, 128 * ti, bar(BAR_XR));
        tma2d(sb + OFF_XR + 16384, &maps.x32, kh ? orem : omain + 48, 128 * ti, bar(BAR_XR));
        mbar_wait_long(bar(BAR_O_W), 0);
        flag_add(FL_O + ti * 2 + kh);
        PROF(14);
        flag_poll(FL_O + ti * 2 + kh, 4 * ep);
        mbar_arrive(bar(BAR_O_RDY));
        flag_poll(FL_Z + ti * 4 + nt, 2 * ep);
        asm volatile("fence.acq_rel.gpu;\nfence.proxy.async;" ::: "memory");
        mbar_arrive(bar(BAR_ZERO));
        PROF(4);
      }
    } else {
      if (lane < (int)(sizeof(Maps) / sizeof(CUtensorMap))) prefetch_map((const CUtensorMap*)&maps + lane);
      __syncwarp();
      cluster_wait();
      {
        Ring r{0, 0};
#pragma unroll 1
        for (int e = 0; e < 40; e++) {
          mbar_wait_long(bar(BAR_B_EMPTY + r.slot), r.phase);
          if (elect_one()) mbar_arrive_cluster(bar(BAR_B_PEER + r.slot), rank ^ 1);
          r.next<B_N>();
        }
#pragma unroll 1
        for (int e = 0; e < B2_STEPS - (int)B2_N; e++) {
          mbar_wait_long(bar(BAR_B2_EMPTY + (e & 7)), (e >> 3) & 1);
          if (elect_one()) mbar_arrive_cluster(bar(BAR_B2_PEER + (e & 7)), rank ^ 1);
        }
        mbar_wait_long(bar(BAR_DONE), 0);
      }
    }
  } else {
    asm volatile("setmaxnreg.inc.sync.aligned.u32 224;");
    const int w = warp >> 2, wq = warp & 3;
    const int g = lane >> 2, tq = lane & 3;
    PROFW(0);
    GT(20);

    const int row_lo = 128 * ti + 64 * w + 16 * wq + g;
    const bool lane0 = lane == 0;
    const uint32_t d0 = (sb & 0x3FFFF) >> 4;
    const uint32_t d128 = d0 + w * (8192 >> 4);
    const uint32_t d64 = d0 + w * (4096 >> 4);

    Ring ra{0, 0}, rb{0, 0};
    uint32_t prev_a = 0, prev_b = 0;
    auto wait_a = [&]() {
      mbar_wait(bar(BAR_A_FULL + ra.slot), ra.phase);
    };
    auto wait_b = [&]() {
      mbar_wait(bar(BAR_B_FULL + rb.slot), rb.phase);
    };
    auto a_desc = [&]() { return d128 + dlo(OFF_A, 16) + ra.slot * (A_SLOT >> 4); };
    auto b_desc = [&]() { return d0 + (OFF_B >> 4) + rb.slot * (B_SLOT >> 4); };
    auto nop = []() {};
    auto step1 = [&](auto HF, auto DEFER, auto&& k0, auto&& k1, bool first, bool last, auto&& hook_a, auto&& hook_b) {
      constexpr int hf = HF.v;
      const uint32_t ad = a_desc(), bd = b_desc();
      const uint32_t cur_a = ra.slot, cur_b = rb.slot;
      auto release_prev = [&]() {
        mbar_arrive_if(!first && lane0, bar(BAR_B_EMPTY + prev_b));
        if constexpr (hf == 0) mbar_arrive_if(!first && lane0, bar(BAR_A_EMPTY + prev_a));
      };
      STEPT(1);
      INTRA(0);
      __syncwarp();
      wg_fence();
      k0(ad, bd);
      wg_commit();
      rb.next<B_N>();
      if constexpr (hf == 1) ra.next<A_N>();
      if constexpr (!DEFER.v) {
        wg_wait<1>();
        release_prev();
      }
      INTRA(1);
      hook_a();
      k1(ad, bd);
      wg_commit();
      INTRA(2);
      if (!last) {
        if constexpr (hf == 1) wait_a();
        wait_b();
      }
      INTRA(3);
      hook_b();
      if constexpr (DEFER.v) {
        wg_wait<2>();
        release_prev();
      }
      INTRAN();
      prev_b = cur_b;
      if constexpr (hf == 1) prev_a = cur_a;
    };
    auto step1r = [&](int hf, auto DEFER, auto&& k0, auto&& k1, bool last, auto&& hook_a, auto&& hook_b) {
      const uint32_t ad = a_desc() + hf * 4, bd = b_desc();
      const uint32_t cur_a = ra.slot, cur_b = rb.slot;
      auto release_prev = [&]() {
        mbar_arrive_if(lane0, bar(BAR_B_EMPTY + prev_b));
        mbar_arrive_if(lane0 && hf == 0, bar(BAR_A_EMPTY + prev_a));
      };
      STEPT(1);
      __syncwarp();
      wg_fence();
      k0(ad, bd);
      wg_commit();
      rb.next<B_N>();
      if (hf == 1) ra.next<A_N>();
      if constexpr (!DEFER.v) {
        wg_wait<1>();
        release_prev();
      }
      hook_a();
      k1(ad, bd);
      wg_commit();
      if (!last) {
        if (hf == 1) wait_a();
        wait_b();
      }
      hook_b();
      if constexpr (DEFER.v) {
        wg_wait<2>();
        release_prev();
      }
      prev_b = cur_b;
      if (hf == 1) prev_a = cur_a;
    };
    auto drain1 = [&]() {
      wg_wait<0>();
      if (lane == 0) { mbar_arrive(bar(BAR_B_EMPTY + prev_b)); mbar_arrive(bar(BAR_A_EMPTY + prev_a)); }
    };

    unsigned ep = 0;
    uint4 sl = make_uint4(0, 0, 0, 0), sh = sl;
    uint32_t hraw[56];
    {
      float acch[112];
      int sc0 = 0;
      auto step_h = [&](auto HF, bool first, bool last, auto&& hook_a, auto&& hook_b) {
        constexpr int hf = HF.v;
        step1(HF, IC<0>{},
              [&](uint32_t ad, uint32_t bd) { wgmma_n224<0, hf * 4, HI128, dlo(0, 2048), HI128>(acch, ad, bd, sc0); sc0 = 1; },
              [&](uint32_t ad, uint32_t bd) { wgmma_n224<0, hf * 4 + 2, HI128, dlo(8192, 2048), HI128>(acch, ad, bd, 1); },
              first, last, hook_a, hook_b);
      };
      float ca[8];
      auto cols_load = [&](auto Q0, auto Q1, uint32_t off) {
        const uint32_t base = sb + OFF_STG + off + tid * 16;
        if constexpr (Q0.v == 0) {
#pragma unroll
          for (int q = 0; q < 8; q++) ca[q] = 0.f;
        }
#pragma unroll
        for (int q = Q0.v; q < Q1.v; q++) {
          uint32_t v0, v1, v2, v3;
          asm volatile("ld.shared.v4.u32 {%0, %1, %2, %3}, [%4];" : "=r"(v0), "=r"(v1), "=r"(v2), "=r"(v3) : "r"(base + q * 4096));
          ca[0] += bf_lo(v0); ca[1] += bf_hi(v0); ca[2] += bf_lo(v1); ca[3] += bf_hi(v1);
          ca[4] += bf_lo(v2); ca[5] += bf_hi(v2); ca[6] += bf_lo(v3); ca[7] += bf_hi(v3);
        }
      };
      auto cols_store = [&](uint32_t dst, uint32_t b) {
        *(float4*)(smem + dst + tid * 32) = make_float4(ca[0], ca[1], ca[2], ca[3]);
        *(float4*)(smem + dst + tid * 32 + 16) = make_float4(ca[4], ca[5], ca[6], ca[7]);
        __syncwarp();
        if (lane == 0) mbar_arrive(bar(b));
      };
      uint32_t xw[2][10];
      float piv[2], sd[2], sdd[2];
      auto rows_load = [&]() {
#pragma unroll
        for (int r = 0; r < 2; r++)
#pragma unroll
          for (int q = 0; q < 5; q++)
            asm volatile("ld.shared.v2.u32 {%0, %1}, [%2];" : "=r"(xw[r][2 * q]), "=r"(xw[r][2 * q + 1])
                         : "r"(sb + OFF_STG + 20480 + q * 4096 + (2 * warp + r) * 256 + lane * 8));
#pragma unroll
        for (int r = 0; r < 2; r++) { piv[r] = __shfl_sync(0xffffffffu, bf_lo(xw[r][0]), 0); sd[r] = 0.f; sdd[r] = 0.f; }
      };
      auto rows_part = [&](auto R, auto HALF) {
        constexpr int r = R.v;
        float s0 = 0.f, s1 = 0.f, t0 = 0.f, t1 = 0.f;
#pragma unroll
        for (int q = 5 * HALF.v; q < 5 * HALF.v + 5; q++) {
          const float d0v = bf_lo(xw[r][q]) - piv[r], d1v = bf_hi(xw[r][q]) - piv[r];
          s0 += d0v; s1 += d1v;
          t0 = fmaf(d0v, d0v, t0); t1 = fmaf(d1v, d1v, t1);
        }
        sd[r] += s0 + s1;
        sdd[r] += t0 + t1;
      };
      auto rows_store = [&]() {
        float* rp = (float*)(smem + OFF_ROWP);
#pragma unroll
        for (int r = 0; r < 2; r++) {
          rp[((2 * warp + r) * 2) * 32 + lane] = sd[r];
          rp[((2 * warp + r) * 2 + 1) * 32 + lane] = sdd[r];
          if (lane == 0) rp[1024 + 2 * warp + r] = piv[r];
        }
        __syncwarp();
        if (lane == 0) mbar_arrive(bar(BAR_ROWP));
      };
      wait_a();
      if (tid == 0) mbar_arrive(bar(BAR_GO));
      wait_b();
      fence_regs(acch);
      wg_fence();
      step_h(IC<0>{}, true, false, nop, nop);
      step_h(IC<1>{}, false, false, nop, nop);
      PROFW(2);
#pragma unroll 1
      for (int kt = 1; kt < 3; kt++) {
        step_h(IC<0>{}, false, false, nop, nop);
        step_h(IC<1>{}, false, false, nop, nop);
      }
      static_for<6, 20>([&](auto Q) {
        constexpr int q = Q.v;
        step_h(IC<(q & 1)>{}, false, q == 19, nop, [&]() {
          if constexpr (q == 7) {
            mbar_wait(bar(BAR_CS_FULL), 0);
            rows_load();
            __syncwarp();
            if (lane == 0) mbar_arrive(bar(BAR_XROWS));
          }
          if constexpr (q == 8) cols_load(IC<0>{}, IC<3>{}, 0);
          if constexpr (q == 9) { cols_load(IC<3>{}, IC<5>{}, 0); cols_store(OFF_COLP, BAR_PROL); PROFW(1); }
          if constexpr (q == 10) rows_part(IC<0>{}, IC<0>{});
          if constexpr (q == 11) rows_part(IC<0>{}, IC<1>{});
          if constexpr (q == 12) rows_part(IC<1>{}, IC<0>{});
          if constexpr (q == 13) { rows_part(IC<1>{}, IC<1>{}); rows_store(); }
          if constexpr (q == 16) { mbar_wait(bar(BAR_CS2_FULL), 0); cols_load(IC<0>{}, IC<3>{}, 20480); }
          if constexpr (q == 17) {
            cols_load(IC<3>{}, IC<5>{}, 20480);
            mbar_wait(bar(BAR_COLC), 0);
            cols_store(OFF_STG + 49152, BAR_PROL2);
          }
          if constexpr (q == 18) {
            mbar_wait(bar(BAR_EPOCH), 0);
            ep = *(volatile unsigned*)(smem + OFF_EPOCH);
            sl = ld_b128(&g_stats[row_lo]); sh = ld_b128(&g_stats[row_lo + 8]);
          }
        });
      });
      cluster_wait();
      drain1();
      fence_regs(acch);
      PROFW(7);
      {
        uint32_t spins = 0;
        while (!__all_sync(0xffffffffu, sl.w == ep && sh.w == ep)) {
          sl = ld_b128(&g_stats[row_lo]); sh = ld_b128(&g_stats[row_lo + 8]);
          if (++spins > (1u << 22)) __trap();
        }
      }
      mbar_wait(bar(BAR_AUX), 0);
      {
        const float ml = -__uint_as_float(sl.y), mh = -__uint_as_float(sh.y);
#pragma unroll
        for (int t = 0; t < 28; t++) {
          const float2 c = lds64f(sb + OFF_C1 + (8 * t + 2 * tq) * 4);
          hraw[2 * t] = pack_bf16(fmaf(ml, c.x, acch[4 * t]), fmaf(ml, c.y, acch[4 * t + 1]));
          hraw[2 * t + 1] = pack_bf16(fmaf(mh, c.x, acch[4 * t + 2]), fmaf(mh, c.y, acch[4 * t + 3]));
        }
      }
    }

    uint32_t qp[10][2];
    {
      float acc[120];
      int sc0 = 0;
      auto step_qd = [&](auto HF, auto DEFER, bool first, bool last, auto&& hook_a, auto&& hook_b) {
        constexpr int hf = HF.v;
        step1(HF, DEFER,
              [&](uint32_t ad, uint32_t bd) {
                wgmma_n192<0, hf * 4, HI128, dlo(0, 2048), HI128>(acc, ad, bd, sc0);
                wgmma_n48<96, hf * 4, HI128, dlo(6144, 512), HI32>(acc, ad, bd, sc0);
                sc0 = 1;
              },
              [&](uint32_t ad, uint32_t bd) {
                wgmma_n192<0, hf * 4 + 2, HI128, dlo(8192, 2048), HI128>(acc, ad, bd, 1);
                wgmma_n48<96, hf * 4 + 2, HI128, dlo(8192 + 6144, 512), HI32>(acc, ad, bd, 1);
              },
              first, last, hook_a, hook_b);
      };
      auto step_q = [&](auto HF, bool first, bool last, auto&& hook_a, auto&& hook_b) { step_qd(HF, IC<0>{}, first, last, hook_a, hook_b); };
      uint32_t chl = 0, chh = 0;
      GeluAddr ga;
      {
        const int m = lane >> 3, row = 16 * wq + (m & 1) * 8 + (lane & 7);
        ga.row128 = sb + OFF_STG + w * 8192 + row * 128;
        ga.x128 = ((row & 7) ^ (m >> 1)) << 4;
        ga.row64 = sb + OFF_STG + 49152 + w * 4096 + row * 64;
        ga.x64 = (((row >> 1) & 3) ^ (m >> 1)) << 4;
        ga.cb = sb + OFF_B1 + (lane & 3) * 4;
      }
      wait_a();
      wait_b();
      fence_regs(acc);
      wg_fence();
      step_q(IC<0>{}, true, false, nop, nop);
      step_q(IC<1>{}, false, false, nop,
             [&]() {
               const float hl = 0.5f * __uint_as_float(sl.z), hh = 0.5f * __uint_as_float(sh.z);
               chl = pack_bf16(hl, hl);
               chh = pack_bf16(hh, hh);
               mbar_wait(bar(BAR_PROL2), 0);
             });
      int hf = 0;
      auto step_r = [&](auto DEFER, bool last, auto&& hook_a, auto&& hook_b) {
        step1r(hf, DEFER,
               [&](uint32_t ad, uint32_t bd) {
                 wgmma_n192<0, 0, HI128, dlo(0, 2048), HI128>(acc, ad, bd, 1);
                 wgmma_n48<96, 0, HI128, dlo(6144, 512), HI32>(acc, ad, bd, 1);
               },
               [&](uint32_t ad, uint32_t bd) {
                 wgmma_n192<0, 2, HI128, dlo(8192, 2048), HI128>(acc, ad, bd, 1);
                 wgmma_n48<96, 2, HI128, dlo(8192 + 6144, 512), HI32>(acc, ad, bd, 1);
               },
               last, hook_a, hook_b);
        hf ^= 1;
      };
      if (w == FK_LATE_WG) step_r(IC<0>{}, false, nop, nop);
      static_for<2, 16>([&](auto Q) {
        constexpr int q = Q.v, kt = q / 2;
        if constexpr ((q & 1) == 0) {
          constexpr int T = kt == 3 ? 0 : kt == 4 ? 1 : kt == 6 ? 2 : kt == 7 ? 3 : -1;
          step_r(IC<0>{}, false,
                 [&]() {
                   if constexpr (q == 10) mbar_wait(bar(BAR_AUX2), 0);
                 },
                 [&]() {
                   if constexpr (T >= 0) {
                     fence_async_smem();
                     __syncwarp();
                     if (lane == 0) mbar_arrive(bar(BAR_HT0 + T));
                     if constexpr (T == 3) PROFW(8);
                   }
                 });
        } else {
          constexpr int n = kt > 6 ? 0 : (kt == 2 || kt == 3) ? 3 : 2;
          constexpr int p0 = kt == 1 ? 0 : kt == 2 ? 2 : kt == 3 ? 5 : kt == 4 ? 8 : kt == 5 ? 10 : 12;
          GeluConst kc[3];
          GeluStage gs[3];
          step_r(IC<(n > 0)>{}, false,
                 [&]() { static_for<0, n>([&](auto I) { gelu_ld<2 * (p0 + I.v)>(kc[I.v], ga); }); },
                 [&]() {
                   static_for<0, n>([&](auto I) { gelu_arg<2 * (p0 + I.v)>(gs[I.v], kc[I.v], hraw, chl, chh); });
                   static_for<0, n>([&](auto I) { gelu_out<2 * (p0 + I.v)>(gs[I.v], ga); });
                 });
        }
      });
#pragma unroll 1
      for (int q = (w == FK_LATE_WG) ? 17 : 16; q < 20; q++) step_r(IC<0>{}, q == 19, nop, nop);
      drain1();
      fence_regs(acc);
      PROFW(3);
      uint32_t qkv[60];
      mbar_wait(bar(BAR_AUX2), 0);
      const float ml = -__uint_as_float(sl.y), mh = -__uint_as_float(sh.y);
      const float rl = __uint_as_float(sl.x), rh = __uint_as_float(sh.x);
      auto ln_tile = [&](auto T, uint32_t al, uint32_t ah) {
        constexpr int t = T.v;
        const float2 c = lds64f(sb + OFF_C + (8 * t + 2 * tq) * 4);
        qkv[2 * t] = mul2(pack_bf16(fmaf(ml, c.x, acc[4 * t]), fmaf(ml, c.y, acc[4 * t + 1])), al);
        qkv[2 * t + 1] = mul2(pack_bf16(fmaf(mh, c.x, acc[4 * t + 2]), fmaf(mh, c.y, acc[4 * t + 3])), ah);
      };
      mbar_wait(bar(BAR_HDONE), 0);
      {
        const uint32_t al = pack_bf16(rl, rl), ah = pack_bf16(rh, rh);
        const int m = lane >> 3;
        const uint32_t st = sb + OFF_STG + (16 + 64 * w + 16 * wq + (m & 1) * 8 + (lane & 7)) * KV_PITCH + (m >> 1) * 16;
        const uint32_t st_main = st + (jodd ? 32 : 0), st_rem = st + (jodd ? 0 : 128);
        static_for<0, 10>([&](auto I) {
          constexpr int isv = I.v / 5, rel = 2 * (I.v % 5), rest = rel == 8, t2 = rest ? 26 + 2 * isv : 8 + 8 * isv + rel;
          ln_tile(IC<t2>{}, al, ah);
          ln_tile(IC<t2 + 1>{}, al, ah);
          stsm4((rest ? st_rem : st_main + rel * 16) + isv * 160, qkv[2 * t2], qkv[2 * t2 + 1], qkv[2 * t2 + 2], qkv[2 * t2 + 3]);
        });
      }
      __syncwarp();
      if (lane == 0) mbar_arrive(bar(BAR_KV));
      if (warp == 7 && ti < 15) {
        uint4* halo = g_halo + (ti * 8 + tj) * (14 * 32) + lane;
        auto word = [&](int u) -> uint32_t {
          const int isv = u / 20, rel = u % 20;
          return u >= 40 ? 0u : (rel < 16 ? qkv[16 + 16 * isv + rel] : qkv[52 + 4 * isv + rel - 16]);
        };
#pragma unroll
        for (int p = 0; p < 14; p++) st_b128(halo + p * 32, word(3 * p), word(3 * p + 1), word(3 * p + 2), ep);
      }
      {
        const float qs = 0.22360679775f * 1.44269504089f;
        const uint32_t al = pack_bf16(rl * qs, rl * qs), ah = pack_bf16(rh * qs, rh * qs);
        static_for<0, 8>([&](auto T) { ln_tile(T, al, ah); });
        ln_tile(IC<24>{}, al, ah);
        ln_tile(IC<25>{}, al, ah);
#pragma unroll
        for (int t = 0; t < 10; t++) {
          const int ev = t < 8 ? t : 16 + t, od = t < 2 ? 24 + t : t - 2;
          qp[t][0] = jodd ? qkv[2 * od] : qkv[2 * ev];
          qp[t][1] = jodd ? qkv[2 * od + 1] : qkv[2 * ev + 1];
        }
      }
    }
    PROFW(4);

    float acc2[80];
    int u2 = 0;
    int sc2 = 0;
    auto wait_a2 = [&]() {
      wait_a();
    };
    auto wait_b2 = [&]() {
      mbar_wait(bar(BAR_B2_FULL + (u2 & 7)), (u2 >> 3) & 1);
    };
    auto step2 = [&](auto KIND, bool new_a, bool rel_a, bool last, auto&& hook_a, auto&& hook_b) {
      constexpr int kind = KIND.v;
      const uint32_t ad = (kind == 2 ? d64 : d128) + dlo(OFF_A, 16) + ra.slot * (A_SLOT >> 4);
      const uint32_t bd = d0 + (OFF_B >> 4) + ((u2 + 6) & 7) * (B2_SLOT >> 4);
      const uint32_t cur_a = ra.slot;
      constexpr uint32_t ahi = kind == 2 ? HI64 : HI128, ao = kind == 1 ? 4 : 0;
      STEPT(3);
      __syncwarp();
      wg_fence();
      wgmma_n160<0, ao, ahi, dlo(0, 2048), HI128>(acc2, ad, bd, sc2);
      sc2 = 1;
      wg_commit();
      u2++;
      if (new_a) ra.next<A_N>();
      wg_wait<1>();
      mbar_arrive_if(lane0 && u2 >= 2 && u2 - 2 < B2_STEPS - (int)B2_N, bar(BAR_B2_EMPTY + ((u2 - 2) & 7)));
      mbar_arrive_if(lane0 && rel_a, bar(BAR_A_EMPTY + prev_a));
      hook_a();
      wgmma_n160<0, ao + 2, ahi, dlo(6144, 2048), HI128>(acc2, ad, bd, 1);
      wg_commit();
      if (!last) {
        if (new_a) wait_a2();
        wait_b2();
      }
      hook_b();
      if (new_a) prev_a = cur_a;
    };
    auto tile2 = [&](bool first) {
      step2(IC<0>{}, false, !first, false, nop, nop);
      step2(IC<1>{}, true, false, false, nop, nop);
    };
    wait_a2();
    wait_b2();
    fence_regs(acc2);
    wg_fence();
    {
      const int e = g & 1;
      const int key0 = 128 * ti + 64 * w + 16 * wq - 16;
      uint32_t vmask = 0;
#pragma unroll
      for (int kt = 0; kt < 4; kt++) {
        const int c = 8 * kt + 2 * tq + e;
        const int dl = g + 16 - c, dh = g + 24 - c;
        if (dl >= 0 && dl <= 14 && key0 + c >= 0) vmask |= 1u << kt;
        if (dh >= 0 && dh <= 14 && key0 + c >= 0) vmask |= 16u << kt;
      }
      const uint32_t kv_ld = sb + OFF_STG + (64 * w + 16 * wq + lane) * KV_PITCH;
      const uint32_t kv_ld2 = sb + OFF_STG + (64 * w + 16 * wq + (lane >> 4) * 8 + (lane & 7)) * KV_PITCH + ((lane >> 3) & 1) * 16;
      uint4 hv[14];
      uint32_t op[10][2];
      const uint4* hsrc = g_halo + ((ti - 1) * 8 + tj) * (14 * 32) + lane;
      static_for<0, 12>([&](auto Q) {
        constexpr int q = Q.v, hf = q & 1;
        if constexpr (q == 6) { if (fs.wide) step2(IC<2>{}, true, true, false, nop, nop); }
        step2(IC<hf>{}, hf == 1, hf == 0 && q != 0, false, nop,
              [&]() {
                if constexpr (q == FK_HALO_Q) {
#pragma unroll
                  for (int p = 0; p < 14; p++) {
                    hv[p] = make_uint4(0, 0, 0, ep);
                    ld_b128_if(hv[p], hsrc + p * 32, warp == 0 && ti > 0);
                  }
                }
                if constexpr (q == FK_ATT_Q - 1) {
                  if (warp == 0) {
                    uint32_t spins = 0;
                    while (true) {
                      uint32_t bad = hv[13].y | hv[13].z;
#pragma unroll
                      for (int p = 0; p < 14; p++) bad |= hv[p].w ^ ep;
                      if (__all_sync(0xffffffffu, bad == 0)) break;
#pragma unroll
                      for (int p = 0; p < 14; p++) hv[p] = ld_b128(hsrc + p * 32);
                      if (++spins > (1u << 22)) __trap();
                    }
                    const int m = lane >> 3;
                    const uint32_t hd = sb + OFF_STG + ((m & 1) * 8 + (lane & 7)) * KV_PITCH + (m >> 1) * 16;
                    const uint32_t hm = hd + (jodd ? 32 : 0), hr = hd + (jodd ? 0 : 128);
                    auto word = [&](int u) -> uint32_t { return (u % 3 == 0) ? hv[u / 3].x : (u % 3 == 1) ? hv[u / 3].y : hv[u / 3].z; };
#pragma unroll
                    for (int u = 0; u < 40; u += 4) {
                      const int rel = u % 20;
                      stsm4((rel < 16 ? hm + (rel >> 1) * 16 : hr) + (u / 20) * 160, word(u), word(u + 1), word(u + 2), word(u + 3));
                    }
                    __syncwarp();
                  }
                }
                if constexpr (q == FK_ATT_Q) {
                  mbar_wait(bar(BAR_KV), 0);
                  PROFW(5);
                  {
                    Attn a0, a1;
                    attn_scores<0>(a0, qp, kv_ld, kv_ld2, tq);
                    attn_scores<2>(a1, qp, kv_ld, kv_ld2, tq);
                    attn_softmax(a0, a1, vmask, e);
                    attn_values<0>(a0, op, kv_ld, tq);
                    attn_values<2>(a1, op, kv_ld, tq);
                  }
                  __syncwarp();
                  if (lane == 0) mbar_arrive(bar(BAR_ATT));
                }
                if constexpr (q == FK_ATT_Q + 1) {
                  mbar_wait(bar(BAR_ATT), 0);
                  const int m = lane >> 3;
                  const uint32_t oa = sb + OFF_STG + (64 * w + 16 * wq + (m & 1) * 8 + (lane & 7)) * 160 + (m >> 1) * 16;
#pragma unroll
                  for (int t = 0; t < 10; t += 2) stsm4(oa + t * 16, op[t][0], op[t][1], op[t + 1][0], op[t + 1][1]);
                  fence_async_smem();
                  __syncwarp();
                  PROFW(6);
                }
                if constexpr (q >= FK_ATT_Q + 1 && q < FK_ATT_Q + 5) {
                  if (wq == q - (FK_ATT_Q + 1) && lane == 0) {
                    tma2d_store(&maps.o_st, 80 * tj, 128 * ti + 64 * w + 16 * wq, sb + OFF_STG + (64 * w + 16 * wq) * 160);
                    asm volatile("cp.async.bulk.commit_group;" ::: "memory");
                  }
                }
                if constexpr (q == FK_ATT_Q + 6) {
                  if (lane == 0) { asm volatile("cp.async.bulk.wait_group 0;" ::: "memory"); mbar_arrive(bar(BAR_O_W)); }
                }
              });
      });
      if (f_slice(4 * kh + ((nt + 1) & 3)).wide) step2(IC<2>{}, true, true, false, nop, nop);
    }
    PROFW(9);
#pragma unroll 1
    for (int s = 2; s < 4; s++) {
#pragma unroll 1
      for (int t = 0; t < 3; t++) tile2(false);
      if (f_slice(4 * kh + ((nt + s) & 3)).wide) step2(IC<2>{}, true, true, false, nop, nop);
    }
    PROFW(10);
    float xb[40];
    step2(IC<0>{}, false, true, false, nop, nop);
    step2(IC<1>{}, true, false, false, nop, [&]() {
      mbar_wait(bar(BAR_XR), 0);
      const int rl = 64 * w + 16 * wq + g;
      static_for<0, 10>([&](auto R) {
        constexpr int r = R.v;
        uint32_t x0, x1, bw;
        const uint32_t xa = r < 6 ? sb + OFF_XR + rl * 128 + ((r ^ (rl & 7)) << 4) + tq * 4
                                  : sb + OFF_XR + 16384 + rl * 64 + (((r - 6) ^ ((rl >> 1) & 3)) << 4) + tq * 4;
        asm volatile("ld.shared.u32 %0, [%1];" : "=r"(x0) : "r"(xa));
        asm volatile("ld.shared.u32 %0, [%1];" : "=r"(x1) : "r"(xa + (r < 6 ? 8 * 128 : 8 * 64)));
        asm volatile("ld.shared.u32 %0, [%1];" : "=r"(bw) : "r"(sb + OFF_B2 + (r * 4 + tq) * 4));
        xb[4 * r] = bf_lo(bw) + bf_lo(x0); xb[4 * r + 1] = bf_hi(bw) + bf_hi(x0);
        xb[4 * r + 2] = bf_lo(bw) + bf_lo(x1); xb[4 * r + 3] = bf_hi(bw) + bf_hi(x1);
      });
    });
    step2(IC<0>{}, false, true, false, nop, nop);
    step2(IC<1>{}, true, false, false, nop, nop);
    PROFW(14);
    if (w == 1) asm volatile("bar.sync 5, 256;" ::: "memory");
    PROFW(15);
    __syncwarp();
    wg_fence();
#pragma unroll 1
    for (int t = 2; t < 5; t++) {
      const uint32_t ad = d128 + dlo(OFF_A, 16) + ra.slot * (A_SLOT >> 4);
      if (t > 2) wait_a2();
#pragma unroll
      for (int hf = 0; hf < 2; hf++) {
        if (t > 2 || hf > 0) wait_b2();
        const uint32_t bd = d0 + (OFF_B >> 4) + ((u2 + 6) & 7) * (B2_SLOT >> 4);
        if (hf == 0) {
          wgmma_n160<0, 0, HI128, dlo(0, 2048), HI128>(acc2, ad, bd, 1);
          wgmma_n160<0, 2, HI128, dlo(6144, 2048), HI128>(acc2, ad, bd, 1);
        } else {
          wgmma_n160<0, 4, HI128, dlo(0, 2048), HI128>(acc2, ad, bd, 1);
          wgmma_n160<0, 6, HI128, dlo(6144, 2048), HI128>(acc2, ad, bd, 1);
        }
        u2++;
      }
      ra.next<A_N>();
    }
    wg_commit();
    PROFW(16);
    if (w == 0) asm volatile("bar.arrive 5, 256;" ::: "memory");
    wg_wait<0>();
    fence_regs(acc2);
    PROFW(11);
    GT(21);

    {
#pragma unroll
      for (int r = 0; r < 40; r++) {
        if (kh) acc2[40 + r] += xb[r];
        else acc2[r] += xb[r];
      }
      PROFW(12);
      const int m = lane >> 3, row = 16 * wq + (m & 1) * 8 + (lane & 7);
      const uint32_t o128 = sb + OFF_A + w * 8192 + row * 128, x128 = ((row & 7) ^ (m >> 1)) << 4;
      const uint32_t o64 = sb + OFF_A + 32768 + w * 8192 + row * 64, x64 = (((row >> 1) & 3) ^ (m >> 1)) << 4;
#pragma unroll
      for (int t = 0; t < 20; t += 2) {
        const uint32_t addr = t < 16 ? o128 + (t >> 3) * 16384 + (x128 ^ ((t & 7) << 4)) : o64 + (x64 ^ ((t - 16) << 4));
        stsm4(addr, pack_bf16(acc2[4 * t], acc2[4 * t + 1]), pack_bf16(acc2[4 * t + 2], acc2[4 * t + 3]),
              pack_bf16(acc2[4 * t + 4], acc2[4 * t + 5]), pack_bf16(acc2[4 * t + 6], acc2[4 * t + 7]));
      }
      __syncwarp();
      mbar_wait(bar(BAR_ZERO), 0);
      {
        bf16* orow = out + (size_t)(128 * ti + 64 * w + 16 * wq) * kD;
        const int r8 = lane >> 3, c8 = lane & 7;
#pragma unroll
        for (int t = 0; t < 2; t++)
#pragma unroll
          for (int u = 0; u < 4; u++) {
            const int r = 4 * u + r8;
            uint32_t v0, v1, v2, v3;
            asm volatile("ld.shared.v4.u32 {%0, %1, %2, %3}, [%4];" : "=r"(v0), "=r"(v1), "=r"(v2), "=r"(v3)
                         : "r"(sb + OFF_A + t * 16384 + w * 8192 + (16 * wq + r) * 128 + ((c8 ^ (r & 7)) << 4)));
            asm volatile("red.relaxed.gpu.global.add.noftz.v4.bf16x2 [%0], {%1, %2, %3, %4};"
                         ::"l"(orow + (size_t)r * kD + omain + 64 * t + 8 * c8), "r"(v0), "r"(v1), "r"(v2), "r"(v3) : "memory");
          }
        const int r4 = lane >> 2, c4 = lane & 3;
#pragma unroll
        for (int u = 0; u < 2; u++) {
          const int r = 8 * u + r4;
          uint32_t v0, v1, v2, v3;
          asm volatile("ld.shared.v4.u32 {%0, %1, %2, %3}, [%4];" : "=r"(v0), "=r"(v1), "=r"(v2), "=r"(v3)
                       : "r"(sb + OFF_A + 32768 + w * 8192 + (16 * wq + r) * 64 + ((c4 ^ ((r >> 1) & 3)) << 4)));
          asm volatile("red.relaxed.gpu.global.add.noftz.v4.bf16x2 [%0], {%1, %2, %3, %4};"
                       ::"l"(orow + (size_t)r * kD + orem + 8 * c4), "r"(v0), "r"(v1), "r"(v2), "r"(v3) : "memory");
        }
      }
      PROFW(13);
    }
    __syncwarp();
    if (lane == 0) mbar_arrive(bar(BAR_DONE));
    cluster_sync_tail();
    GT(23);
  }
}

typedef CUresult (*EncodeFn)(CUtensorMap*, CUtensorMapDataType, cuuint32_t, void*, const cuuint64_t*, const cuuint64_t*,
                             const cuuint32_t*, const cuuint32_t*, CUtensorMapInterleave, CUtensorMapSwizzle,
                             CUtensorMapL2promotion, CUtensorMapFloatOOBfill);

static void encode(EncodeFn fn, CUtensorMap* m, const void* base, int rank, const cuuint64_t* dims,
                   const cuuint64_t* strides, const cuuint32_t* box, CUtensorMapSwizzle sw) {
  const cuuint32_t es[3] = {1, 1, 1};
  fn(m, CU_TENSOR_MAP_DATA_TYPE_BFLOAT16, rank, const_cast<void*>(base), dims, strides, box, es,
     CU_TENSOR_MAP_INTERLEAVE_NONE, sw, CU_TENSOR_MAP_L2_PROMOTION_L2_128B, CU_TENSOR_MAP_FLOAT_OOB_FILL_NONE);
}

}

extern "C" void kernel_launch(void* const* d_in, const int* in_sizes, int n_in, void* d_out, int out_size) {
  using namespace fk;
  (void)in_sizes; (void)n_in; (void)out_size;
  const bf16* x = (const bf16*)d_in[0];
  const bf16* wqkv = (const bf16*)d_in[1];
  const bf16* wo = (const bf16*)d_in[2];
  const bf16* w1 = (const bf16*)d_in[4];
  const bf16* b1 = (const bf16*)d_in[5];
  const bf16* w2 = (const bf16*)d_in[6];
  const bf16* b2 = (const bf16*)d_in[7];

  static EncodeFn enc = nullptr;
  static void* o_ptr = nullptr;
  static void* h_ptr = nullptr;
  if (!enc) {
    void* fn = nullptr;
    cudaDriverEntryPointQueryResult qr;
    cudaGetDriverEntryPoint("cuTensorMapEncodeTiled", &fn, cudaEnableDefault, &qr);
    enc = (EncodeFn)fn;
    cudaGetSymbolAddress(&o_ptr, g_o);
    cudaGetSymbolAddress(&h_ptr, g_h);
    cudaFuncSetAttribute(fused_kernel, cudaFuncAttributeMaxDynamicSharedMemorySize, SMEM_BYTES);
  }
  Maps m;
  const CUtensorMapSwizzle S128 = CU_TENSOR_MAP_SWIZZLE_128B, S64 = CU_TENSOR_MAP_SWIZZLE_64B, S32 = CU_TENSOR_MAP_SWIZZLE_32B;
  {
    const cuuint64_t d[2] = {640, 2048}, s[1] = {1280};
    const cuuint32_t b[2] = {64, 128};
    encode(enc, &m.x, x, 2, d, s, b, S128);
    encode(enc, &m.o, o_ptr, 2, d, s, b, S128);
  }
  {
    const cuuint64_t d[3] = {640, 640, 3}, s[2] = {3840, 1280};
    const cuuint32_t bm[3] = {64, 16, 3}, br[3] = {16, 16, 3};
    encode(enc, &m.wqkv_m, wqkv, 3, d, s, bm, S128);
    encode(enc, &m.wqkv_r, wqkv, 3, d, s, br, S32);
  }
  {
    const cuuint64_t d[3] = {1600, 640, 3}, s[2] = {3456, 128};
    const cuuint32_t bm[3] = {64, 16, 3};
    encode(enc, &m.w1_m, w1, 3, d, s, bm, S128);
    const cuuint64_t d2[2] = {1728, 640}, s2[1] = {3456};
    const cuuint32_t br[2] = {32, 16};
    encode(enc, &m.w1_r, w1, 2, d2, s2, br, S128);
  }
  {
    const cuuint64_t s[2] = {1280, 128}, s2[1] = {1280};
    const cuuint32_t bm[3] = {64, 16, 2}, br[2] = {32, 16};
    const cuuint64_t do3[3] = {576, 640, 2}, do2[2] = {640, 640};
    encode(enc, &m.wo_m, wo, 3, do3, s, bm, S128);
    encode(enc, &m.wo_r, wo, 2, do2, s2, br, S128);
    const cuuint64_t d23[3] = {576, 1728, 2}, d22[2] = {640, 1728};
    encode(enc, &m.w2_m, w2, 3, d23, s, bm, S128);
    encode(enc, &m.w2_r, w2, 2, d22, s2, br, S128);
  }
  {
    const cuuint64_t d[2] = {1728, 2048}, s[1] = {3456};
    const cuuint32_t bl[2] = {64, 128}, bl32[2] = {32, 128};
    encode(enc, &m.h_ml, h_ptr, 2, d, s, bl, S128);
    encode(enc, &m.h_rl, h_ptr, 2, d, s, bl32, S64);
  }
  {
    const cuuint64_t dq[2] = {1920, 640}, sq[1] = {3840}, d1[2] = {1728, 640}, s1[1] = {3456};
    const cuuint32_t b[2] = {16, 160};
    encode(enc, &m.cs_q, wqkv, 2, dq, sq, b, CU_TENSOR_MAP_SWIZZLE_NONE);
    encode(enc, &m.cs_1, w1, 2, d1, s1, b, CU_TENSOR_MAP_SWIZZLE_NONE);
    const cuuint64_t dx[2] = {640, 2048}, sx[1] = {1280};
    const cuuint32_t bx[2] = {128, 16};
    encode(enc, &m.xs, x, 2, dx, sx, bx, CU_TENSOR_MAP_SWIZZLE_NONE);
    const cuuint32_t bo[2] = {80, 16};
    encode(enc, &m.o_st, o_ptr, 2, dx, sx, bo, CU_TENSOR_MAP_SWIZZLE_NONE);
    const cuuint32_t b32x[2] = {32, 128};
    encode(enc, &m.x32, x, 2, dx, sx, b32x, S64);
    const cuuint32_t bo64[2] = {64, 16}, bo32[2] = {32, 16};
    encode(enc, &m.out64, d_out, 2, dx, sx, bo64, S128);
    encode(enc, &m.out32, d_out, 2, dx, sx, bo32, S64);
  }
  cudaLaunchConfig_t cfg = {};
  cfg.gridDim = dim3(kCtas);
  cfg.blockDim = dim3(kThreads);
  cfg.dynamicSmemBytes = SMEM_BYTES;
  cfg.stream = cudaStreamPerThread;
  cudaLaunchAttribute attr[1];
  attr[0].id = cudaLaunchAttributeClusterDimension;
  attr[0].val.clusterDim.x = 2;
  attr[0].val.clusterDim.y = 1;
  attr[0].val.clusterDim.z = 1;
  cfg.attrs = attr;
  cfg.numAttrs = 1;
  cudaLaunchKernelEx(&cfg, fused_kernel, m, x, wqkv, wo, w1, b1, w2, b2, (bf16*)d_out);
}
```
